```python
import torch

def _softmax(x, axis=-1):
    return torch.softmax(x, dim=axis)
def _gelu(x):
    return torch.nn.functional.gelu(x, approximate="tanh")
def _silu(x):
    return torch.nn.functional.silu(x)
def _sigmoid(x):
    return torch.sigmoid(x)
def _layernorm(x, axis=-1, eps=1e-5):
    m = x.mean(dim=axis, keepdim=True)
    v = x.var(dim=axis, keepdim=True, unbiased=False)
    return (x - m) / torch.sqrt(v + eps)
def _scatter_add(tgt, idx, src, axis=0):
    return tgt.clone().index_add_(axis, idx, src)
def _segment_sum(src, seg, n):
    out = torch.zeros((n,) + src.shape[1:], dtype=src.dtype)
    return out.index_add_(0, seg, src)
def _pad(x, pw):
    flat = tuple(v for pair in reversed(pw) for v in pair)
    return torch.nn.functional.pad(x, flat)

kernel_name = 'gated_mix__sliding_block_cached__mixer_channel_mlp__decode'

def setup_inputs():

    _w = (lambda a: (lambda t: t.to(torch.bfloat16) if t.is_floating_point() else t)(torch.as_tensor(a)))
    def _A_setup():
        B, Sq, D = 8, 1, 448
        Hq, Hkv, Sk, Dh = 16, 8, 4096, 256
        assert Hq % Hkv == 0, (Hq, Hkv)
        return {
            "x": _w((lambda *s: torch.randn(*s, dtype=torch.bfloat16) * 0.05)(B, Sq, D)),
            "k_cache": _w((lambda *s: torch.randn(*s, dtype=torch.bfloat16) * 6.4)(B, Hkv, Sk, Dh)),
            "v_cache": _w((lambda *s: torch.randn(*s, dtype=torch.bfloat16) * 0.4)(B, Hkv, Sk, Dh)),
            "wq": _w((lambda *s: torch.randn(*s, dtype=torch.bfloat16) * 6.4)(D, Hq * Dh) * (D ** -0.5)),
            "wo": _w((lambda *s: torch.randn(*s, dtype=torch.bfloat16) * 0.4)(Hq * Dh, D) * ((Hq * Dh) ** -0.5)),
        }
    _A_in = _A_setup()

    def _B_setup():
        B, S, D, F = 8, 1, 448, 1792
        return {
            "x": _w((lambda *s: torch.randn(*s, dtype=torch.bfloat16) * 0.05)(B, S, D)),
            "w1": _w((lambda *s: torch.randn(*s, dtype=torch.bfloat16) * 0.8)(D, F) * (D ** -0.5)),
            "b1": _w((lambda *s: torch.randn(*s, dtype=torch.bfloat16) * 0.8)(F)),
            "w2": _w((lambda *s: torch.randn(*s, dtype=torch.bfloat16) * 0.05)(F, D) * (F ** -0.5)),
            "b2": _w((lambda *s: torch.randn(*s, dtype=torch.bfloat16) * 0.05)(D)),
        }
    _B_in = _B_setup()

    return {
        "A_x": _A_in["x"],
        "A_k_cache": _A_in["k_cache"],
        "A_v_cache": _A_in["v_cache"],
        "A_wq": _A_in["wq"],
        "A_wo": _A_in["wo"],
        "B_x": _B_in["x"],
        "B_w1": _B_in["w1"],
        "B_b1": _B_in["b1"],
        "B_w2": _B_in["w2"],
        "B_b2": _B_in["b2"],
        "gate_w": _w((lambda *s: torch.randn(*s, dtype=torch.bfloat16) * 0.05)(448) * 16.0),
    }

def reference(A_x, A_k_cache, A_v_cache, A_wq, A_wo, B_x, B_w1, B_b1, B_w2, B_b2, gate_w):
    def _A_ref(x, k_cache, v_cache, wq, wo):
        B, Sq, D = x.shape
        Hq, Dh = 16, 256
        Hkv, Sk = k_cache.shape[1], k_cache.shape[2]
        W = min(4096, max(256, Sk // 4))
        rep = Hq // Hkv
        q = (lambda x, *d: x.permute(*d))((x @ wq).reshape(B, Sq, Hq, Dh), 0, 2, 1, 3)
        k = (lambda x, n, axis: torch.repeat_interleave(x, n, dim=axis))(k_cache[:, :, Sk - W:, :], rep, axis=1)
        v = (lambda x, n, axis: torch.repeat_interleave(x, n, dim=axis))(v_cache[:, :, Sk - W:, :], rep, axis=1)
        scores = torch.einsum("bhqd,bhkd->bhqk", q, k) * (Dh ** -0.5)
        p = _softmax(scores, axis=-1)
        o = torch.einsum("bhqk,bhkd->bhqd", p, v)
        return (lambda x, *d: x.permute(*d))(o, 0, 2, 1, 3).reshape(B, Sq, Hq * Dh) @ wo

    def _B_ref(x, w1, b1, w2, b2):
        y = _layernorm(x, axis=-1)
        h = _gelu(torch.einsum("bsd,df->bsf", y, w1) + b1)
        return torch.einsum("bsf,fd->bsd", h, w2) + b2

    x = A_x
    g = _sigmoid((x * gate_w).sum(-1, keepdims=True))
    a = _A_ref(x, A_k_cache, A_v_cache, A_wq, A_wo)
    b = _B_ref(x, B_w1, B_b1, B_w2, B_b2)
    return g * a + (1 - g) * b
```

```cpp
#include <cuda_runtime.h>
#include <cuda_bf16.h>
#include <cuda.h>
#include <stdint.h>

namespace {

constexpr int D_MODEL = 448;
constexpr int N_QCOL = 4096;
constexpr int SK = 4096;
constexpr int WIN = 1024;
constexpr int FF = 1792;
constexpr int NCTA = 128;

constexpr int ROW_BYTES = 512;
constexpr int TILE_ROWS = 32;
constexpr int TILE_BYTES = TILE_ROWS * ROW_BYTES;
constexpr int NS = 12;
constexpr int NT = 512 / TILE_ROWS;
constexpr int POS_K = 2, POS_W1 = POS_K + NT, POS_V = POS_W1 + 1, POS_W2 = POS_V + NT, POS_WO = POS_W2 + 1;
static_assert(POS_WO % NS + 2 <= NS, "wo tile must not wrap");
#define DEPTH_A 3
#define DEPTH_B 10
#define POLL_BACKOFF
#define PUMP_GAP 150
#define PACE_NS 660
#define PACE_T0 300
#define PRE_IT 3
constexpr int NTHREADS = 416;
constexpr int POS_GO = POS_V + 6;
constexpr int XS_PITCH = 912;

constexpr int OFF_RING = 0;
constexpr int OFF_U = NS * TILE_BYTES;
constexpr int OFF_XS = OFF_U + 8192;
constexpr int OFF_YS = OFF_U + 16384;
constexpr int OFF_OS = OFF_YS;
constexpr int OFF_PS = OFF_YS + 8192;
constexpr int OFF_QS = OFF_PS + 4096;
constexpr int OFF_HR = OFF_QS + 1024;
constexpr int OFF_ST = OFF_HR + 2048;
constexpr int OFF_WM = OFF_ST + 64;
constexpr int OFF_WS = OFF_WM + 64;
constexpr int OFF_TG = OFF_WS + 64;
constexpr int OFF_BAR = OFF_TG + 16;
constexpr int NBAR = 2 * NS + 5;
constexpr int SMEM_USED = OFF_BAR + NBAR * 8;
constexpr int SMEM_BYTES = SMEM_USED + 1024;

constexpr unsigned SPIN_LIMIT = 1u << 22;

__device__ unsigned g_epoch;
__device__ __align__(128) unsigned long long g_qbuf[8 * 8 * 256];
__device__ __align__(128) unsigned long long g_hbuf[16 * 7 * 32 * 2];
__device__ __align__(128) unsigned long long g_mlbuf[NCTA * 4];
__device__ __align__(128) unsigned long long g_obuf[16 * 2 * 8 * 32 * 2];
__device__ __align__(128) uint4 g_pbuf[7 * 16 * 16 * 8];

#define TS(i) do { } while (0)
#define TSR(i) do { } while (0)
#define TSW(i) do { } while (0)

__device__ __forceinline__ uint32_t gtime32() { uint32_t t; asm volatile("mov.u32 %0, %globaltimer_lo;" : "=r"(t)); return t; }
__device__ __forceinline__ void spin_cycles(uint32_t n) {
    uint32_t t0, t;
    asm volatile("mov.u32 %0, %clock;" : "=r"(t0));
    do { asm volatile("mov.u32 %0, %clock;" : "=r"(t)); } while (t - t0 < n);
}
__device__ __forceinline__ void mbar_init(uint32_t bar, int cnt) {
    asm volatile("mbarrier.init.shared::cta.b64 [%0], %1;" :: "r"(bar), "r"(cnt) : "memory");
}
__device__ __forceinline__ void mbar_expect_tx(uint32_t bar, uint32_t bytes) {
    asm volatile("mbarrier.arrive.expect_tx.shared::cta.b64 _, [%0], %1;" :: "r"(bar), "r"(bytes) : "memory");
}
__device__ __forceinline__ void mbar_arrive(uint32_t bar) {
    asm volatile("mbarrier.arrive.shared::cta.b64 _, [%0];" :: "r"(bar) : "memory");
}
__device__ __forceinline__ void mbar_arrive_n(uint32_t bar, uint32_t n) {
    asm volatile("mbarrier.arrive.shared::cta.b64 _, [%0], %1;" :: "r"(bar), "r"(n) : "memory");
}
__device__ __forceinline__ bool mbar_try(uint32_t bar, uint32_t parity) {
    uint32_t ok;
    asm volatile("{\n.reg .pred p;\nmbarrier.try_wait.parity.shared::cta.b64 p, [%1], %2;\nselp.u32 %0, 1, 0, p;\n}"
                 : "=r"(ok) : "r"(bar), "r"(parity) : "memory");
    return ok != 0;
}
__device__ __forceinline__ bool mbar_test(uint32_t bar, uint32_t parity) {
    uint32_t ok;
    asm volatile("{\n.reg .pred p;\nmbarrier.test_wait.parity.shared::cta.b64 p, [%1], %2;\nselp.u32 %0, 1, 0, p;\n}"
                 : "=r"(ok) : "r"(bar), "r"(parity) : "memory");
    return ok != 0;
}
__device__ __forceinline__ void mbar_wait(uint32_t bar, uint32_t parity) {
    unsigned n = 0;
    while (!mbar_try(bar, parity)) { if (++n > SPIN_LIMIT) __trap(); }
}
__device__ __forceinline__ void bulk_g2s(uint32_t dst, const void* src, uint32_t bytes, uint32_t bar) {
    asm volatile("cp.async.bulk.shared::cluster.global.mbarrier::complete_tx::bytes [%0], [%1], %2, [%3];"
                 :: "r"(dst), "l"(src), "r"(bytes), "r"(bar) : "memory");
}
#define tma_2d_real tma_2d
__device__ __forceinline__ void tma_2d_real(uint32_t dst, const CUtensorMap* map, int c0, int c1, uint32_t bar) {
    asm volatile("cp.async.bulk.tensor.2d.shared::cluster.global.mbarrier::complete_tx::bytes [%0], [%1, {%3, %4}], [%2];"
                 :: "r"(dst), "l"(map), "r"(bar), "r"(c0), "r"(c1) : "memory");
}
__device__ __forceinline__ void bar_sync(int id, int n) { asm volatile("bar.sync %0, %1;" :: "r"(id), "r"(n) : "memory"); }
__device__ __forceinline__ void bar_arrive(int id, int n) { asm volatile("bar.arrive %0, %1;" :: "r"(id), "r"(n) : "memory"); }

__device__ __forceinline__ uint4 lds128(uint32_t a) {
    uint4 v; asm volatile("ld.shared.v4.u32 {%0,%1,%2,%3}, [%4];" : "=r"(v.x), "=r"(v.y), "=r"(v.z), "=r"(v.w) : "r"(a) : "memory"); return v;
}
__device__ __forceinline__ uint2 lds64(uint32_t a) {
    uint2 v; asm volatile("ld.shared.v2.u32 {%0,%1}, [%2];" : "=r"(v.x), "=r"(v.y) : "r"(a) : "memory"); return v;
}
__device__ __forceinline__ float lds32f(uint32_t a) {
    float v; asm volatile("ld.shared.f32 %0, [%1];" : "=f"(v) : "r"(a) : "memory"); return v;
}
__device__ __forceinline__ uint32_t lds32u(uint32_t a) {
    uint32_t v; asm volatile("ld.shared.u32 %0, [%1];" : "=r"(v) : "r"(a) : "memory"); return v;
}
__device__ __forceinline__ bool elect_one() {
    uint32_t p;
    asm volatile("{\n.reg .pred p;\nelect.sync _|p, 0xffffffff;\nselp.u32 %0, 1, 0, p;\n}" : "=r"(p));
    return p != 0;
}
__device__ __forceinline__ void sts128(uint32_t a, uint32_t x, uint32_t y, uint32_t z, uint32_t w) {
    asm volatile("st.shared.v4.u32 [%0], {%1,%2,%3,%4};" :: "r"(a), "r"(x), "r"(y), "r"(z), "r"(w) : "memory");
}
__device__ __forceinline__ void sts128f(uint32_t a, float x, float y, float z, float w) {
    asm volatile("st.shared.v4.f32 [%0], {%1,%2,%3,%4};" :: "r"(a), "f"(x), "f"(y), "f"(z), "f"(w) : "memory");
}
__device__ __forceinline__ void sts64(uint32_t a, uint32_t x, uint32_t y) {
    asm volatile("st.shared.v2.u32 [%0], {%1,%2};" :: "r"(a), "r"(x), "r"(y) : "memory");
}
__device__ __forceinline__ void sts64f(uint32_t a, float x, float y) {
    asm volatile("st.shared.v2.f32 [%0], {%1,%2};" :: "r"(a), "f"(x), "f"(y) : "memory");
}
__device__ __forceinline__ void sts32(uint32_t a, uint32_t x) {
    asm volatile("st.shared.u32 [%0], %1;" :: "r"(a), "r"(x) : "memory");
}
__device__ __forceinline__ void ldsm_x4_t(uint32_t a, uint32_t& r0, uint32_t& r1, uint32_t& r2, uint32_t& r3) {
    asm volatile("ldmatrix.sync.aligned.m8n8.x4.trans.shared.b16 {%0,%1,%2,%3}, [%4];"
                 : "=r"(r0), "=r"(r1), "=r"(r2), "=r"(r3) : "r"(a) : "memory");
}
__device__ __forceinline__ void mma16816(float (&c)[4], uint32_t a0, uint32_t a1, uint32_t a2, uint32_t a3,
                                         uint32_t b0, uint32_t b1) {
    asm volatile("mma.sync.aligned.m16n8k16.row.col.f32.bf16.bf16.f32 {%0,%1,%2,%3}, {%4,%5,%6,%7}, {%8,%9}, {%0,%1,%2,%3};"
                 : "+f"(c[0]), "+f"(c[1]), "+f"(c[2]), "+f"(c[3])
                 : "r"(a0), "r"(a1), "r"(a2), "r"(a3), "r"(b0), "r"(b1));
}
__device__ __forceinline__ uint32_t lo_pair(uint32_t a, uint32_t b) { return __byte_perm(a, b, 0x5410); }
__device__ __forceinline__ uint32_t hi_pair(uint32_t a, uint32_t b) { return __byte_perm(a, b, 0x7632); }
__device__ __forceinline__ float bf_lo(uint32_t v) { return __uint_as_float(v << 16); }
__device__ __forceinline__ float bf_hi(uint32_t v) { return __uint_as_float(v & 0xffff0000u); }
__device__ __forceinline__ float bf_round(float x) { return __bfloat162float(__float2bfloat16_rn(x)); }
__device__ __forceinline__ uint32_t pack_bf(float lo, float hi) {
    uint32_t r; asm("cvt.rn.bf16x2.f32 %0, %1, %2;" : "=r"(r) : "f"(hi), "f"(lo)); return r;
}
__device__ __forceinline__ uint2 ldg_nc64(const void* p) {
    uint2 v; asm volatile("ld.global.nc.L1::no_allocate.L2::128B.v2.u32 {%0,%1}, [%2];" : "=r"(v.x), "=r"(v.y) : "l"(p)); return v;
}
__device__ __forceinline__ uint32_t ldg_nc32(const void* p) {
    uint32_t v; asm volatile("ld.global.nc.L1::no_allocate.L2::128B.u32 %0, [%1];" : "=r"(v) : "l"(p)); return v;
}
__device__ __forceinline__ unsigned long long pkt(uint32_t payload, uint32_t tag) {
    return ((unsigned long long)tag << 32) | payload;
}
__device__ __forceinline__ void st_pkt(unsigned long long* p, unsigned long long v) {
    asm volatile("st.relaxed.gpu.global.u64 [%0], %1;" :: "l"(p), "l"(v) : "memory");
}
__device__ __forceinline__ void st_pkt2(unsigned long long* p, unsigned long long a, unsigned long long b) {
    asm volatile("st.relaxed.gpu.global.v2.u64 [%0], {%1,%2};" :: "l"(p), "l"(a), "l"(b) : "memory");
}
__device__ __forceinline__ unsigned long long ld_pkt(const unsigned long long* p) {
    unsigned long long v; asm volatile("ld.relaxed.gpu.global.u64 %0, [%1];" : "=l"(v) : "l"(p) : "memory"); return v;
}
__device__ __forceinline__ void ld_pkt2(const unsigned long long* p, unsigned long long& a, unsigned long long& b) {
    asm volatile("ld.relaxed.gpu.global.v2.u64 {%0,%1}, [%2];" : "=l"(a), "=l"(b) : "l"(p) : "memory");
}
__device__ __forceinline__ void st_v4(uint4* p, uint32_t a, uint32_t b, uint32_t c, uint32_t d) {
    asm volatile("st.relaxed.gpu.global.v4.u32 [%0], {%1,%2,%3,%4};" :: "l"(p), "r"(a), "r"(b), "r"(c), "r"(d) : "memory");
}
__device__ __forceinline__ uint4 ld_v4(const uint4* p) {
    uint4 v;
    asm volatile("ld.relaxed.gpu.global.v4.u32 {%0,%1,%2,%3}, [%4];" : "=r"(v.x), "=r"(v.y), "=r"(v.z), "=r"(v.w) : "l"(p) : "memory");
    return v;
}
__device__ __forceinline__ uint32_t hadd2_bf(uint32_t a, uint32_t b) {
    uint32_t r; asm("add.rn.bf16x2 %0, %1, %2;" : "=r"(r) : "r"(a), "r"(b)); return r;
}
__device__ __forceinline__ uint32_t tag_of(unsigned long long v) { return (uint32_t)(v >> 32); }
__device__ __forceinline__ uint32_t pay_of(unsigned long long v) { return (uint32_t)v; }

__device__ __forceinline__ float gelu_tanh(float x) {
    float u = 0.7978845608028654f * (x + 0.044715f * x * x * x);
    return 0.5f * x * (1.0f + tanhf(u));
}

#define LB_THREADS NTHREADS
__global__ void __launch_bounds__(LB_THREADS, 1)
fused_kernel(const __nv_bfloat16* __restrict__ x, const char* __restrict__ kc, const char* __restrict__ vc,
             const __nv_bfloat16* __restrict__ b1, const __nv_bfloat16* __restrict__ b2,
             const __nv_bfloat16* __restrict__ gw, __nv_bfloat16* __restrict__ out,
             const __grid_constant__ CUtensorMap map_wq, const __grid_constant__ CUtensorMap map_w1,
             const __grid_constant__ CUtensorMap map_wo, const __grid_constant__ CUtensorMap map_w2) {
    extern __shared__ unsigned char smem_raw[];
    uint32_t sb = ((uint32_t)__cvta_generic_to_shared(smem_raw) + 1023u) & ~1023u;
    asm volatile("" : "+r"(sb));
    const int tid = threadIdx.x, warp = tid >> 5, lane = tid & 31;
    const int c = blockIdx.x;
    const int hkv = c >> 4, b = (c >> 1) & 7, s = c & 1;
    const int rho = c >> 3, cg = c & 7;
    const int fs = rho * 7 + cg;
    const uint32_t bar_full = sb + OFF_BAR, bar_empty = bar_full + NS * 8, bar_w = bar_empty + NS * 8;

    if (warp == 8) {
        const size_t kv_off = ((size_t)(b * 8 + hkv) * SK + (SK - WIN) + s * 512) * ROW_BYTES;
        const char* src = kc + kv_off;
        const bool leader = elect_one();
        if (leader) {
#pragma unroll
            for (int i = 0; i < DEPTH_A; i++) mbar_init(bar_full + i * 8, 1);
            asm volatile("fence.mbarrier_init.release.cluster;" ::: "memory");
            mbar_expect_tx(bar_full, 224 * 64);
            TS(11);
            tma_2d(sb + OFF_RING, &map_wq, 32 * c, 0, bar_full);
            TS(12);
            mbar_expect_tx(bar_full + 8, 224 * 64);
            tma_2d(sb + OFF_RING + 224 * 64, &map_wq, 32 * c, 224, bar_full + 8);
#pragma unroll
            for (int i = POS_K; i < DEPTH_A; i++) {
                mbar_expect_tx(bar_full + i * 8, TILE_BYTES);
                bulk_g2s(sb + OFF_RING + i * TILE_BYTES, src + (i - POS_K) * TILE_BYTES, TILE_BYTES, bar_full + i * 8);
            }
            TS(13);
#pragma unroll
            for (int i = DEPTH_A; i < NS; i++) mbar_init(bar_full + i * 8, 1);
#pragma unroll
            for (int i = 0; i < NS; i++) mbar_init(bar_empty + i * 8, 4);
#pragma unroll
            for (int i = 0; i < 5; i++) mbar_init(bar_w + i * 8, 1);
            asm volatile("fence.mbarrier_init.release.cluster;" ::: "memory");
        }
        __syncwarp();
        if (leader) TS(14);
        bar_arrive(2, NTHREADS);
        const int ob = 2 * (lane & 3) + ((lane >> 3) & 1);
        const int ocol = 64 * cg + 16 * (rho >> 2) + 2 * (rho & 3) + ((lane >> 2) & 1) + 8 * (lane >> 4);
        unsigned short b2v = 0;
        if (cg < 7) b2v = *reinterpret_cast<const unsigned short*>(b2 + ocol);
        if (leader) {
            asm volatile("prefetch.tensormap [%0];" :: "l"(&map_w1) : "memory");
            asm volatile("prefetch.tensormap [%0];" :: "l"(&map_w2) : "memory");
            asm volatile("prefetch.tensormap [%0];" :: "l"(&map_wo) : "memory");
        }
        {
            int slot = DEPTH_A, ph = 1;
            int landed = 0, lslot = 0, lph = 0, depth = DEPTH_A;
            uint32_t due = (uint32_t)gtime32() + PACE_T0;
            auto acquire = [&](int pos) {
                while ((int)(gtime32() - due) < 0) { }
                due += PACE_NS;
                depth = DEPTH_B;
                if (depth == DEPTH_A && mbar_test(bar_empty + POS_K * 8, 0)) depth = DEPTH_B;
                if (pos - landed >= depth && landed < POS_W2) {
                    mbar_wait(bar_full + lslot * 8, lph);
                    landed++;
                    if (++lslot == NS) { lslot = 0; lph ^= 1; }
                }
                if (pos >= NS) mbar_wait(bar_empty + slot * 8, ph);
            };
            src += (DEPTH_A - POS_K) * TILE_BYTES;
#pragma unroll 1
            for (int pos = DEPTH_A; pos < POS_W2; pos++) {
                acquire(pos);
                const uint32_t dst = sb + OFF_RING + slot * TILE_BYTES, bar = bar_full + slot * 8;
                if (pos == POS_GO && leader) mbar_arrive(bar_w + 32);
                if (pos == POS_W1) {
                    if (leader) {
                        if (cg < 7) {
                            mbar_expect_tx(bar, 448 * 32);
                            tma_2d(dst, &map_w1, 16 * fs, 0, bar);
                            tma_2d(dst + 224 * 32, &map_w1, 16 * fs, 224, bar);
                        } else {
                            mbar_arrive(bar);
                        }
                    }
                    src = vc + kv_off;
                } else {
                    if (leader) {
                        mbar_expect_tx(bar, TILE_BYTES);
                        bulk_g2s(dst, src, TILE_BYTES, bar);
                    }
                    src += TILE_BYTES;
                }
                if (++slot == NS) { slot = 0; ph ^= 1; }
            }
            if (cg == 7) return;
            acquire(POS_W2);
            if (leader) {
                mbar_expect_tx(bar_w, 112 * 128);
                tma_2d(sb + OFF_RING + (POS_W2 % NS) * TILE_BYTES, &map_w2, 64 * cg, 112 * rho, bar_w);
            }
            if (++slot == NS) { slot = 0; ph ^= 1; }
            const uint32_t wdst = sb + OFF_RING + (POS_WO % NS) * TILE_BYTES;
            acquire(POS_WO);
            if (leader) {
                mbar_expect_tx(bar_w + 8, 4 * 4096);
#pragma unroll
                for (int i = 0; i < 4; i++) tma_2d(wdst + i * 4096, &map_wo, 64 * cg, 256 * rho + 32 * i, bar_w + 8);
            }
            if (++slot == NS) { slot = 0; ph ^= 1; }
            acquire(POS_WO + 1);
            if (leader) {
                mbar_expect_tx(bar_w + 16, 3 * 4096);
                mbar_expect_tx(bar_w + 24, 4096);
#pragma unroll
                for (int i = 4; i < 8; i++) tma_2d(wdst + i * 4096, &map_wo, 64 * cg, 256 * rho + 32 * i, bar_w + (i < 7 ? 16 : 24));
            }
        }
        {
            const uint32_t tag = lds32u(sb + OFF_TG), par = tag & 1;
            const float bias = lds32f(sb + OFF_ST + ob * 8 + 4) * __uint_as_float((uint32_t)b2v << 16);
            const uint4* psrc = &g_pbuf[(cg * 16 + rho) * 128 + lane];
            bar_sync(4, 160);
            TSR(22);
            unsigned n = 0;
            uint4 A[4], B[4], C[4];
            auto issue = [&](uint4 (&X)[4]) {
#pragma unroll
                for (int i = 0; i < 4; i++) X[i] = ld_v4(psrc + i * 32);
            };
            auto ready = [&](const uint4 (&X)[4]) {
                uint32_t all1 = 1, any1 = 0;
#pragma unroll
                for (int i = 0; i < 4; i++) {
                    all1 &= X[i].x & X[i].y & X[i].z & X[i].w;
                    any1 |= X[i].x | X[i].y | X[i].z | X[i].w;
                }
                return __all_sync(0xffffffffu, ((par ? all1 : ~any1) & 1) != 0);
            };
            issue(A); spin_cycles(PUMP_GAP);
            issue(B); spin_cycles(PUMP_GAP);
            issue(C);
            while (true) {
                if (ready(A)) break;
                issue(A);
                if (ready(B)) {
#pragma unroll
                    for (int i = 0; i < 4; i++) A[i] = B[i];
                    break;
                }
                issue(B);
                if (ready(C)) {
#pragma unroll
                    for (int i = 0; i < 4; i++) A[i] = C[i];
                    break;
                }
                issue(C);
                if (++n > SPIN_LIMIT) __trap();
            }
#define PV(i, f) __uint_as_float(A[i].f & ~1u)
            const float e0 = (PV(0, x) + PV(1, x)) + (PV(2, x) + PV(3, x)), e1 = (PV(0, y) + PV(1, y)) + (PV(2, y) + PV(3, y));
            const float e2 = (PV(0, z) + PV(1, z)) + (PV(2, z) + PV(3, z)), e3 = (PV(0, w) + PV(1, w)) + (PV(2, w) + PV(3, w));
#undef PV
            const bool up = lane & 16, up2 = lane & 8;
            const float k0 = (up ? e2 : e0) + __shfl_xor_sync(0xffffffffu, up ? e0 : e2, 16);
            const float k1 = (up ? e3 : e1) + __shfl_xor_sync(0xffffffffu, up ? e1 : e3, 16);
            const float r = (up2 ? k1 : k0) + __shfl_xor_sync(0xffffffffu, up2 ? k0 : k1, 8) + bias;
            out[ob * D_MODEL + ocol] = __float2bfloat16_rn(r);
            if (c == 0 && lane == 0) asm volatile("st.relaxed.gpu.global.u32 [%0], %1;" :: "l"(&g_epoch), "r"(tag) : "memory");
        }
        return;
    }

    if (warp > 8) {
        const int mt = warp - 9;
        bar_sync(2, NTHREADS);
        if (cg == 7) return;
        mbar_wait(bar_w + 32, 0);
        const uint32_t tag = lds32u(sb + OFF_TG), par = tag & 1;
        uint4* const pdst = &g_pbuf[((cg * 16 + 4 * mt + (lane >> 3)) * 16 + rho) * 8 + (lane & 7)];
        st_v4(pdst, par ^ 1, par ^ 1, par ^ 1, par ^ 1);
        uint32_t hf[7][2];
        {
            const unsigned long long* hsrc = &g_hbuf[(rho * 7 * 32 + lane) * 2];
            unsigned n = 0; bool ok;
            do {
                unsigned long long ha[7], hb[7];
#pragma unroll
                for (int i = 0; i < 7; i++) ld_pkt2(hsrc + i * 64, ha[i], hb[i]);
                ok = true;
#pragma unroll
                for (int i = 0; i < 7; i++) {
                    ok = ok && tag_of(ha[i]) == tag && tag_of(hb[i]) == tag;
                    hf[i][0] = pay_of(ha[i]); hf[i][1] = pay_of(hb[i]);
                }
                if (++n > SPIN_LIMIT) __trap();
            } while (!__all_sync(0xffffffffu, ok));
        }
        const uint32_t aoff = ((lane & 7) + ((lane >> 4) << 3)) * 128 + (((2 * mt + ((lane >> 3) & 1)) ^ (lane & 7)) << 4);
        float cc[4][4];
#pragma unroll
        for (int i = 0; i < 4; i++) { cc[i][0] = cc[i][1] = cc[i][2] = cc[i][3] = 0.f; }
        const unsigned long long* osrc = &g_obuf[((rho * 2 * 8 + 2 * mt) * 32 + lane) * 2];
        unsigned long long pa[4], pb[4];
        mbar_wait(bar_w, 0);
        ld_pkt2(osrc, pa[0], pb[0]);
        ld_pkt2(osrc + 512, pa[1], pb[1]);
        ld_pkt2(osrc + 64, pa[2], pb[2]);
        ld_pkt2(osrc + 512 + 64, pa[3], pb[3]);
        {
            const uint32_t wb = sb + OFF_RING + (POS_W2 % NS) * TILE_BYTES + aoff;
#pragma unroll
            for (int i = 0; i < 7; i++) {
                uint32_t a0, a1, a2, a3;
                ldsm_x4_t(wb + i * 2048, a0, a1, a2, a3);
                mma16816(cc[i & 3], a0, a1, a2, a3, hf[i][0], hf[i][1]);
            }
        }
        const uint32_t wb = sb + OFF_RING + (POS_WO % NS) * TILE_BYTES + aoff;
        uint32_t wf[16][4];
        bool g0 = false, g1 = false, g2 = false;
        auto load_w = [&](int lo, int hi) {
#pragma unroll
            for (int i = 0; i < 16; i++)
                if (i >= lo && i < hi) ldsm_x4_t(wb + i * 2048, wf[i][0], wf[i][1], wf[i][2], wf[i][3]);
        };
        unsigned n = 0;
        while (true) {
            if (!g0 && mbar_test(bar_w + 8, 0)) { load_w(0, 8); g0 = true; }
            if (!g1 && mbar_test(bar_w + 16, 0)) { load_w(8, 14); g1 = true; }
            if (!g2 && mbar_test(bar_w + 24, 0)) { load_w(14, 16); g2 = true; }
            bool okk[4];
#pragma unroll
            for (int i = 0; i < 4; i++) okk[i] = (((uint32_t)pa[i] ^ par) & 1) == 0 && (((uint32_t)pb[i] ^ par) & 1) == 0;
            if (__all_sync(0xffffffffu, okk[0] && okk[1] && okk[2] && okk[3])) break;
            if (!okk[0]) ld_pkt2(osrc, pa[0], pb[0]);
            if (!okk[1]) ld_pkt2(osrc + 512, pa[1], pb[1]);
            if (!okk[2]) ld_pkt2(osrc + 64, pa[2], pb[2]);
            if (!okk[3]) ld_pkt2(osrc + 512 + 64, pa[3], pb[3]);
            if (++n > SPIN_LIMIT) __trap();
        }
#pragma unroll
        for (int i = 0; i < 2; i++) {
            sts128(sb + OFF_OS + (2 * mt + i) * 512 + lane * 16,
                   hadd2_bf((uint32_t)pa[2 * i] & ~1u, (uint32_t)pa[2 * i + 1] & ~1u),
                   hadd2_bf((uint32_t)(pa[2 * i] >> 32), (uint32_t)(pa[2 * i + 1] >> 32)),
                   hadd2_bf((uint32_t)pb[2 * i] & ~1u, (uint32_t)pb[2 * i + 1] & ~1u),
                   hadd2_bf((uint32_t)(pb[2 * i] >> 32), (uint32_t)(pb[2 * i + 1] >> 32)));
        }
        bar_sync(4, 160);
        TSR(7);
        uint4 of[8];
#pragma unroll
        for (int i = 0; i < 8; i++) of[i] = lds128(sb + OFF_OS + i * 512 + lane * 16);
        auto mm = [&](int lo, int hi) {
#pragma unroll
            for (int i = 0; i < 16; i++)
                if (i >= lo && i < hi)
                    mma16816(cc[i & 3], wf[i][0], wf[i][1], wf[i][2], wf[i][3],
                             (i & 1) ? of[i >> 1].z : of[i >> 1].x, (i & 1) ? of[i >> 1].w : of[i >> 1].y);
        };
        if (!g0) { mbar_wait(bar_w + 8, 0); load_w(0, 8); }
        mm(0, 8);
        if (!g1) { mbar_wait(bar_w + 16, 0); load_w(8, 14); }
        mm(8, 14);
        if (!g2) { mbar_wait(bar_w + 24, 0); load_w(14, 16); }
        mm(14, 16);
        uint32_t res[4];
#pragma unroll
        for (int e = 0; e < 4; e++)
            res[e] = (__float_as_uint((cc[0][e] + cc[1][e]) + (cc[2][e] + cc[3][e])) & ~1u) | par;
        st_v4(pdst, res[0], res[1], res[2], res[3]);
        return;
    }

    const int g = lane >> 2, t = lane & 3;
    uint32_t epoch;
    asm volatile("ld.relaxed.gpu.global.u32 %0, [%1];" : "=r"(epoch) : "l"(&g_epoch) : "memory");
    unsigned long long* const qdst = &g_qbuf[(hkv * 8 + ((tid >> 4) & 7)) * 256 + (c & 15) * 16 + (tid & 15)];
    if (tid < 128) st_pkt(qdst, 0ull);
    uint32_t b1v = 0;
    if (cg < 7) b1v = *reinterpret_cast<const uint32_t*>(b1 + 16 * fs + 2 * (((tid >> 1) & 3) + 4 * (tid & 1)));

    {
        uint32_t xr[7], gr[7];
#pragma unroll
        for (int i = 0; i < 7; i++) {
            xr[i] = *reinterpret_cast<const uint32_t*>(x + warp * D_MODEL + 2 * (lane + 32 * i));
            gr[i] = *reinterpret_cast<const uint32_t*>(gw + 2 * (lane + 32 * i));
        }
        float sum = 0.f, gz = 0.f;
#pragma unroll
        for (int i = 0; i < 7; i++) {
            sts32(sb + OFF_XS + warp * XS_PITCH + (lane + 32 * i) * 4, xr[i]);
            sum += bf_lo(xr[i]) + bf_hi(xr[i]);
            gz += bf_round(bf_lo(xr[i]) * bf_lo(gr[i])) + bf_round(bf_hi(xr[i]) * bf_hi(gr[i]));
        }
#pragma unroll
        for (int o = 16; o; o >>= 1) { sum += __shfl_xor_sync(0xffffffffu, sum, o); gz += __shfl_xor_sync(0xffffffffu, gz, o); }
        const float mean = sum * (1.0f / D_MODEL);
        float var = 0.f;
#pragma unroll
        for (int i = 0; i < 7; i++) {
            const float d0 = bf_lo(xr[i]) - mean, d1 = bf_hi(xr[i]) - mean;
            var += d0 * d0 + d1 * d1;
        }
#pragma unroll
        for (int o = 16; o; o >>= 1) var += __shfl_xor_sync(0xffffffffu, var, o);
        const float den = bf_round(sqrtf(bf_round(bf_round(var * (1.0f / D_MODEL)) + 1e-5f)));
        const float mb = bf_round(mean);
#pragma unroll
        for (int i = 0; i < 7; i++) {
            sts32(sb + OFF_YS + warp * XS_PITCH + (lane + 32 * i) * 4,
                  pack_bf(__fdividef(bf_round(bf_lo(xr[i]) - mb), den), __fdividef(bf_round(bf_hi(xr[i]) - mb), den)));
        }
        if (lane == 0) {
            const float gt = bf_round(__fdividef(1.0f, 1.0f + __expf(-bf_round(gz))));
            sts64f(sb + OFF_ST + warp * 8, gt, bf_round(1.0f - gt));
        }
    }
    const uint32_t tag = (epoch + 1) ? epoch + 1 : 2;
    if (tid == 0) sts32(sb + OFF_TG, tag);
    bar_sync(2, NTHREADS);
    TSR(0);
    {
        const int mt = warp & 1, kq = warp >> 1;
        const int row = 112 * kq + (lane & 7) + ((lane >> 4) << 3);
        const uint32_t wa = sb + OFF_RING + row * 64 + (((2 * mt + ((lane >> 3) & 1)) ^ ((row >> 1) & 3)) << 4);
        const uint32_t xa = sb + OFF_XS + g * XS_PITCH + (112 * kq + 2 * t) * 2;
        uint32_t xb[7][2];
#pragma unroll
        for (int ks = 0; ks < 7; ks++) { xb[ks][0] = lds32u(xa + ks * 32); xb[ks][1] = lds32u(xa + ks * 32 + 16); }
        mbar_wait(bar_full + (kq >> 1) * 8, 0);
        float c0[4] = {0.f, 0.f, 0.f, 0.f}, c1[4] = {0.f, 0.f, 0.f, 0.f};
#pragma unroll
        for (int ks = 0; ks < 7; ks++) {
            uint32_t a0, a1, a2, a3;
            ldsm_x4_t(wa + ks * 1024, a0, a1, a2, a3);
            if (ks & 1) mma16816(c1, a0, a1, a2, a3, xb[ks][0], xb[ks][1]);
            else mma16816(c0, a0, a1, a2, a3, xb[ks][0], xb[ks][1]);
        }
        sts128f(sb + OFF_U + warp * 512 + lane * 16, c0[0] + c1[0], c0[1] + c1[1], c0[2] + c1[2], c0[3] + c1[3]);
        bar_sync(1, 256);
        if (tid < 128) {
            const int pb = tid >> 4, p = tid & 15;
            const uint32_t ra = sb + OFF_U + (p >> 3) * 512 + (4 * ((2 * p) & 7) + (pb >> 1)) * 16 + ((p >> 2) & 1) * 8 + (pb & 1) * 4;
            float v0 = 0.f, v1 = 0.f;
#pragma unroll
            for (int w = 0; w < 4; w++) { v0 += lds32f(ra + w * 1024); v1 += lds32f(ra + w * 1024 + 64); }
            st_pkt(qdst, pkt(pack_bf(v0, v1), tag));
        } else if (tid == 128) {
            mbar_arrive_n(bar_empty, 4);
            mbar_arrive_n(bar_empty + 8, 4);
        }
    }
    TSR(1);
    {
        const unsigned long long* src = &g_qbuf[(hkv * 8 + b) * 256 + tid];
        unsigned long long v;
        unsigned n = 0;
        do { v = ld_pkt(src); if (++n > SPIN_LIMIT) __trap(); } while (tag_of(v) != tag);
        sts32(sb + OFF_QS + tid * 4, pay_of(v));
    }
    bar_sync(1, 256);
    TSR(2);

    int slot = POS_K + (warp >> 2), ph = 0;
    {
        const int j8 = lane & 7;
        float qr[2][4][8];
#pragma unroll
        for (int h = 0; h < 2; h++)
#pragma unroll
            for (int i = 0; i < 4; i++) {
                const uint4 u = lds128(sb + OFF_QS + h * 512 + i * 128 + j8 * 16);
                qr[h][i][0] = bf_lo(u.x); qr[h][i][1] = bf_hi(u.x); qr[h][i][2] = bf_lo(u.y); qr[h][i][3] = bf_hi(u.y);
                qr[h][i][4] = bf_lo(u.z); qr[h][i][5] = bf_hi(u.z); qr[h][i][6] = bf_lo(u.w); qr[h][i][7] = bf_hi(u.w);
            }
        const uint32_t koff = (8 * (warp & 3) + (lane >> 3)) * ROW_BYTES + j8 * 16;
        const uint32_t soff = sb + OFF_U + (8 * warp + 4 * (j8 >> 2) + (lane >> 3)) * 8 + ((j8 >> 1) & 1) * 4;
#pragma unroll 1
        for (int it = 0; it < 8; it++) {
            mbar_wait(bar_full + slot * 8, ph);
            const uint32_t base = sb + OFF_RING + slot * TILE_BYTES + koff;
            uint4 la[4], lb[4];
#pragma unroll
            for (int i = 0; i < 4; i++) { la[i] = lds128(base + i * 128); lb[i] = lds128(base + 4 * ROW_BYTES + i * 128); }
            float a0 = 0.f, a1 = 0.f, b0 = 0.f, b1_ = 0.f;
#pragma unroll
            for (int i = 0; i < 4; i++) {
                const uint32_t wa[4] = {la[i].x, la[i].y, la[i].z, la[i].w}, wb[4] = {lb[i].x, lb[i].y, lb[i].z, lb[i].w};
#pragma unroll
                for (int e = 0; e < 4; e++) {
                    const float al = bf_lo(wa[e]), ah = bf_hi(wa[e]), bl = bf_lo(wb[e]), bh = bf_hi(wb[e]);
                    a0 = fmaf(al, qr[0][i][2 * e], a0); a1 = fmaf(al, qr[1][i][2 * e], a1);
                    b0 = fmaf(bl, qr[0][i][2 * e], b0); b1_ = fmaf(bl, qr[1][i][2 * e], b1_);
                    a0 = fmaf(ah, qr[0][i][2 * e + 1], a0); a1 = fmaf(ah, qr[1][i][2 * e + 1], a1);
                    b0 = fmaf(bh, qr[0][i][2 * e + 1], b0); b1_ = fmaf(bh, qr[1][i][2 * e + 1], b1_);
                }
            }
            __syncwarp();
            if (lane == 0) mbar_arrive(bar_empty + slot * 8);
            const bool up = j8 & 4;
            float k0 = (up ? b0 : a0) + __shfl_xor_sync(0xffffffffu, up ? a0 : b0, 4);
            float k1 = (up ? b1_ : a1) + __shfl_xor_sync(0xffffffffu, up ? a1 : b1_, 4);
            const bool up2 = j8 & 2;
            float r = (up2 ? k1 : k0) + __shfl_xor_sync(0xffffffffu, up2 ? k0 : k1, 2);
            r += __shfl_xor_sync(0xffffffffu, r, 1);
            if ((lane & 1) == 0) sts32(soff + it * 512, __float_as_uint(r));
            slot += 2; if (slot >= NS) { slot -= NS; ph ^= 1; }
        }
        slot += 1; if (slot >= NS) { slot -= NS; ph ^= 1; }
    }
    if (warp < 4 && cg < 7) {
        const int row = 112 * warp + (lane & 7) + ((lane >> 4) << 3);
        const uint32_t wa = sb + OFF_RING + (POS_W1 % NS) * TILE_BYTES + row * 32 + ((((lane >> 3) & 1) ^ ((row >> 2) & 1)) << 4);
        const uint32_t ya = sb + OFF_YS + g * XS_PITCH + (112 * warp + 2 * t) * 2;
        mbar_wait(bar_full + (POS_W1 % NS) * 8, (POS_W1 / NS) & 1);
        float c0[4] = {0.f, 0.f, 0.f, 0.f};
#pragma unroll
        for (int ks = 0; ks < 7; ks++) {
            uint32_t a0, a1, a2, a3;
            ldsm_x4_t(wa + ks * 512, a0, a1, a2, a3);
            mma16816(c0, a0, a1, a2, a3, lds32u(ya + ks * 32), lds32u(ya + ks * 32 + 16));
        }
        sts128f(sb + OFF_HR + warp * 512 + lane * 16, c0[0], c0[1], c0[2], c0[3]);
    }
    bar_sync(1, 256);
    TSR(3);
    if (tid == 255) mbar_arrive_n(bar_empty + (POS_W1 % NS) * 8, 4);
    float own_m, own_l;
    {
        const uint4 p0 = lds128(sb + OFF_U + tid * 16);
        const float s00 = bf_round(__uint_as_float(p0.x)) * 0.0625f;
        const float s01 = bf_round(__uint_as_float(p0.y)) * 0.0625f;
        const float s10 = bf_round(__uint_as_float(p0.z)) * 0.0625f;
        const float s11 = bf_round(__uint_as_float(p0.w)) * 0.0625f;
        float m0 = fmaxf(s00, s10), m1 = fmaxf(s01, s11);
#pragma unroll
        for (int o = 16; o; o >>= 1) {
            m0 = fmaxf(m0, __shfl_xor_sync(0xffffffffu, m0, o));
            m1 = fmaxf(m1, __shfl_xor_sync(0xffffffffu, m1, o));
        }
        if (lane == 0) sts64f(sb + OFF_WM + warp * 8, m0, m1);
        if (tid < 64 && cg < 7) {
            const int L = tid >> 1, hf = tid & 1, pb = L >> 2;
            const uint32_t ra = sb + OFF_HR + (4 * (2 * (L & 3)) + (pb >> 1)) * 16 + hf * 8 + (pb & 1) * 4;
            float v0 = 0.f, v1 = 0.f;
#pragma unroll
            for (int w = 0; w < 4; w++) { v0 += lds32f(ra + w * 512); v1 += lds32f(ra + w * 512 + 64); }
            const float omg = lds32f(sb + OFF_ST + pb * 8 + 4);
            v0 = bf_round(gelu_tanh(bf_round(bf_round(v0) + bf_lo(b1v)))) * omg;
            v1 = bf_round(gelu_tanh(bf_round(bf_round(v1) + bf_hi(b1v)))) * omg;
            st_pkt(&g_hbuf[(fs * 32 + L) * 2 + hf], pkt(pack_bf(v0, v1), tag));
        }
        bar_sync(1, 256);
#pragma unroll
        for (int w = 0; w < 4; w++) {
            const uint4 v = lds128(sb + OFF_WM + w * 16);
            m0 = fmaxf(m0, fmaxf(__uint_as_float(v.x), __uint_as_float(v.z)));
            m1 = fmaxf(m1, fmaxf(__uint_as_float(v.y), __uint_as_float(v.w)));
        }
        const float e00 = __expf(s00 - m0), e10 = __expf(s10 - m0), e01 = __expf(s01 - m1), e11 = __expf(s11 - m1);
        sts128f(sb + OFF_PS + tid * 16, e00, e01, e10, e11);
        float l0 = e00 + e10, l1 = e01 + e11;
#pragma unroll
        for (int o = 16; o; o >>= 1) { l0 += __shfl_xor_sync(0xffffffffu, l0, o); l1 += __shfl_xor_sync(0xffffffffu, l1, o); }
        if (lane == 0) sts64f(sb + OFF_WS + warp * 8, l0, l1);
        bar_sync(1, 256);
        const int hh = tid >> 7;
        float l = 0.f;
#pragma unroll
        for (int w = 0; w < 8; w++) l += lds32f(sb + OFF_WS + w * 8 + hh * 4);
        own_m = hh ? m1 : m0; own_l = l;
        if ((tid & 127) == 0)
            st_pkt2(&g_mlbuf[c * 4 + hh * 2], pkt(__float_as_uint(own_m), tag), pkt(__float_as_uint(l), tag));
    }
    TSR(4);
    float acc[2][8];
#pragma unroll
    for (int i = 0; i < 8; i++) { acc[0][i] = acc[1][i] = 0.f; }
    const unsigned long long* msrc = &g_mlbuf[(c ^ 1) * 4 + (tid >> 7) * 2];
    unsigned long long pm = 0, pl = 0;
    float scale = 0.f;
    unsigned long long* const odst =
        &g_obuf[((((2 * hkv + (tid >> 7)) * 2 + s) * 8 + ((tid >> 4) & 7)) * 32 + b * 4 + ((tid >> 1) & 3)) * 2 + ((tid >> 3) & 1)];
    {
        const uint32_t poff = sb + OFF_PS + warp * 64;
        const uint32_t voff = 8 * (warp & 3) * ROW_BYTES + lane * 16;
#pragma unroll 1
        for (int i = 0; i < 8; i++) {
            uint4 pf[4];
#pragma unroll
            for (int j = 0; j < 4; j++) pf[j] = lds128(poff + i * 512 + j * 16);
            if (i == PRE_IT) {
                ld_pkt2(msrc, pm, pl);
                if ((tid & 1) == 0) st_pkt(odst, (unsigned long long)((tag & 1) ^ 1));
            }
            mbar_wait(bar_full + slot * 8, ph);
            const uint32_t base = sb + OFF_RING + slot * TILE_BYTES + voff;
            uint4 r[8];
#pragma unroll
            for (int j = 0; j < 8; j++) r[j] = lds128(base + j * ROW_BYTES);
#pragma unroll
            for (int j = 0; j < 8; j++) {
                const float p0 = __uint_as_float((j & 1) ? pf[j >> 1].z : pf[j >> 1].x);
                const float p1 = __uint_as_float((j & 1) ? pf[j >> 1].w : pf[j >> 1].y);
                const uint32_t wv[4] = {r[j].x, r[j].y, r[j].z, r[j].w};
#pragma unroll
                for (int e = 0; e < 4; e++) {
                    const float lo = bf_lo(wv[e]), hi = bf_hi(wv[e]);
                    acc[0][2 * e] = fmaf(lo, p0, acc[0][2 * e]); acc[1][2 * e] = fmaf(lo, p1, acc[1][2 * e]);
                    acc[0][2 * e + 1] = fmaf(hi, p0, acc[0][2 * e + 1]); acc[1][2 * e + 1] = fmaf(hi, p1, acc[1][2 * e + 1]);
                }
            }
            __syncwarp();
            if (lane == 0) mbar_arrive(bar_empty + slot * 8);
            if (i == 6) {
                unsigned n = 0;
                while (tag_of(pm) != tag || tag_of(pl) != tag) { ld_pkt2(msrc, pm, pl); if (++n > SPIN_LIMIT) __trap(); }
                const float m_o = __uint_as_float(pay_of(pm)), l_o = __uint_as_float(pay_of(pl));
                const float m = fmaxf(own_m, m_o);
                const float e_s = __expf(own_m - m), e_o = __expf(m_o - m);
                scale = __fdividef(lds32f(sb + OFF_ST + b * 8) * e_s, e_s * own_l + e_o * l_o);
            }
            slot += 2; if (slot >= NS) { slot -= NS; ph ^= 1; }
        }
    }
    TSR(5);
    {
        const uint32_t ra = sb + OFF_U + warp * 2048 + lane * 16;
        sts128f(ra, acc[0][0], acc[0][1], acc[0][2], acc[0][3]);
        sts128f(ra + 512, acc[0][4], acc[0][5], acc[0][6], acc[0][7]);
        sts128f(ra + 1024, acc[1][0], acc[1][1], acc[1][2], acc[1][3]);
        sts128f(ra + 1536, acc[1][4], acc[1][5], acc[1][6], acc[1][7]);
        const int hh = tid >> 7, ks = (tid >> 3) & 15, tq = (tid >> 1) & 3, hi = tid & 1;
        const int d = 16 * ks + 8 * hi + 2 * tq;
        const uint32_t rb = sb + OFF_U + hh * 1024 + ((d >> 2) & 1) * 512 + (d >> 3) * 16 + (d & 3) * 4;
        bar_sync(1, 256);
        float v0 = 0.f, v1 = 0.f;
#pragma unroll
        for (int w = 0; w < 8; w++) { const uint2 u = lds64(rb + w * 2048); v0 += __uint_as_float(u.x); v1 += __uint_as_float(u.y); }
        v0 *= scale; v1 *= scale;
        uint32_t word = pack_bf(v0, v1);
        const uint32_t other = __shfl_xor_sync(0xffffffffu, word, 1);
        word = (word & 0xffff0000u) | (((__float_as_uint(v0) + 0x10000u) >> 16) & 0xfffeu) | (tag & 1);
        if (hi == 0) st_pkt(odst, pkt(word, other));
    }
}

typedef CUresult (*EncodeFn)(CUtensorMap*, CUtensorMapDataType, cuuint32_t, void*, const cuuint64_t*, const cuuint64_t*,
                             const cuuint32_t*, const cuuint32_t*, CUtensorMapInterleave, CUtensorMapSwizzle,
                             CUtensorMapL2promotion, CUtensorMapFloatOOBfill);

bool make_map(EncodeFn fn, CUtensorMap* m, const void* ptr, int cols, int rows, int box_cols, int box_rows,
              CUtensorMapSwizzle swz) {
    cuuint64_t dims[2] = {(cuuint64_t)cols, (cuuint64_t)rows};
    cuuint64_t strides[1] = {(cuuint64_t)cols * 2};
    cuuint32_t box[2] = {(cuuint32_t)box_cols, (cuuint32_t)box_rows};
    cuuint32_t es[2] = {1, 1};
    return fn(m, CU_TENSOR_MAP_DATA_TYPE_BFLOAT16, 2, const_cast<void*>(ptr), dims, strides, box, es,
              CU_TENSOR_MAP_INTERLEAVE_NONE, swz, CU_TENSOR_MAP_L2_PROMOTION_L2_128B,
              CU_TENSOR_MAP_FLOAT_OOB_FILL_NONE) == CUDA_SUCCESS;
}

}

extern "C" void kernel_launch(void* const* d_in, const int* in_sizes, int n_in, void* d_out, int out_size) {
    (void)in_sizes; (void)n_in; (void)out_size;
    static EncodeFn enc = nullptr;
    if (!enc) {
        void* fn = nullptr;
        cudaDriverEntryPointQueryResult qr;
        cudaGetDriverEntryPoint("cuTensorMapEncodeTiled", &fn, cudaEnableDefault, &qr);
        enc = (EncodeFn)fn;
        cudaFuncSetAttribute(fused_kernel, cudaFuncAttributeMaxDynamicSharedMemorySize, SMEM_BYTES);
    }
    CUtensorMap map_wq, map_w1, map_wo, map_w2;
    make_map(enc, &map_wq, d_in[3], N_QCOL, D_MODEL, 32, 224, CU_TENSOR_MAP_SWIZZLE_64B);
    make_map(enc, &map_w1, d_in[6], FF, D_MODEL, 16, 224, CU_TENSOR_MAP_SWIZZLE_32B);
    make_map(enc, &map_wo, d_in[4], D_MODEL, N_QCOL, 64, 32, CU_TENSOR_MAP_SWIZZLE_128B);
    make_map(enc, &map_w2, d_in[8], D_MODEL, FF, 64, 112, CU_TENSOR_MAP_SWIZZLE_128B);

    cudaLaunchConfig_t cfg = {};
    cfg.gridDim = dim3(NCTA);
    cfg.blockDim = dim3(LB_THREADS);
    cfg.dynamicSmemBytes = SMEM_BYTES;
    cfg.stream = cudaStreamPerThread;
    cudaLaunchAttribute at[1];
    at[0].id = cudaLaunchAttributeCooperative;
    at[0].val.cooperative = 1;
    cfg.attrs = at;
    cfg.numAttrs = 1;
    cudaLaunchKernelEx(&cfg, fused_kernel,
                       (const __nv_bfloat16*)d_in[0], (const char*)d_in[1], (const char*)d_in[2],
                       (const __nv_bfloat16*)d_in[7], (const __nv_bfloat16*)d_in[9],
                       (const __nv_bfloat16*)d_in[10], (__nv_bfloat16*)d_out, map_wq, map_w1, map_wo, map_w2);
}
```

```cpp
#include <cuda_runtime.h>
#include <cuda_bf16.h>
#include <cuda.h>
#include <stdint.h>

namespace {

constexpr int D_MODEL = 448;
constexpr int N_QCOL = 4096;
constexpr int SK = 4096;
constexpr int WIN = 1024;
constexpr int FF = 1792;
constexpr int NCTA = 128;

constexpr int ROW_BYTES = 512;
constexpr int TILE_ROWS = 32;
constexpr int TILE_BYTES = TILE_ROWS * ROW_BYTES;
constexpr int NS = 12;
constexpr int NT = 512 / TILE_ROWS;
constexpr int POS_K = 2, POS_W1 = POS_K + NT, POS_V = POS_W1 + 1, POS_W2 = POS_V + NT, POS_WO = POS_W2 + 1;
static_assert(POS_WO % NS + 2 <= NS, "wo tile must not wrap");
#define DEPTH_A 3
#define DEPTH_B 10
#define POLL_BACKOFF
#define POLL_START 1
#define BURST_N 0
#define BURST_NS 300
#define WPACE_NS PACE_NS
#define DEPTH_W 10
#define MAXREG 128
#define FINAL_DELAY 0
#define PACE_WGAP 500
#define PACE_NS 650
#define PACE_T0 700
#define PRE_IT 3
constexpr int NTHREADS = 416;
constexpr int POS_GO = POS_V + 6;
constexpr int XS_PITCH = 912;

constexpr int OFF_RING = 0;
constexpr int OFF_U = NS * TILE_BYTES;
constexpr int OFF_XS = OFF_U + 8192;
constexpr int OFF_YS = OFF_U + 16384;
constexpr int OFF_OS = OFF_YS;
constexpr int OFF_PS = OFF_YS + 8192;
constexpr int OFF_QS = OFF_PS + 4096;
constexpr int OFF_HR = OFF_QS + 1024;
constexpr int OFF_ST = OFF_HR + 2048;
constexpr int OFF_WM = OFF_ST + 64;
constexpr int OFF_WS = OFF_WM + 64;
constexpr int OFF_TG = OFF_WS + 64;
constexpr int OFF_BAR = OFF_TG + 16;
constexpr int NBAR = 2 * NS + 7;
constexpr int SMEM_USED = OFF_BAR + NBAR * 8;
constexpr int SMEM_BYTES = SMEM_USED + 1024;

constexpr unsigned SPIN_LIMIT = 1u << 22;

__device__ unsigned g_epoch;
__device__ __align__(128) unsigned long long g_qbuf[8 * 8 * 256];
__device__ __align__(128) unsigned long long g_hbuf[16 * 7 * 32 * 2];
__device__ __align__(128) unsigned long long g_mlbuf[NCTA * 4];
__device__ __align__(128) unsigned long long g_obuf[16 * 2 * 8 * 32 * 2];
__device__ __align__(128) uint4 g_pbuf[7 * 4 * 16 * 32];
__device__ __align__(128) unsigned long long g_acc[7 * 4 * 4 * 32];

#define TS(i) do { } while (0)
#define TSR(i) do { } while (0)
#define TSW(i) do { } while (0)

__device__ __forceinline__ uint32_t gtime32() { uint32_t t; asm volatile("mov.u32 %0, %globaltimer_lo;" : "=r"(t)); return t; }
__device__ __forceinline__ uint32_t clock32() { uint32_t t; asm volatile("mov.u32 %0, %clock;" : "=r"(t)); return t; }
__device__ __forceinline__ void spin_cycles(uint32_t n) {
    uint32_t t0, t;
    asm volatile("mov.u32 %0, %clock;" : "=r"(t0));
    do { asm volatile("mov.u32 %0, %clock;" : "=r"(t)); } while (t - t0 < n);
}
__device__ __forceinline__ void mbar_init(uint32_t bar, int cnt) {
    asm volatile("mbarrier.init.shared::cta.b64 [%0], %1;" :: "r"(bar), "r"(cnt) : "memory");
}
__device__ __forceinline__ void mbar_expect_tx(uint32_t bar, uint32_t bytes) {
    asm volatile("mbarrier.arrive.expect_tx.shared::cta.b64 _, [%0], %1;" :: "r"(bar), "r"(bytes) : "memory");
}
__device__ __forceinline__ void mbar_arrive(uint32_t bar) {
    asm volatile("mbarrier.arrive.shared::cta.b64 _, [%0];" :: "r"(bar) : "memory");
}
__device__ __forceinline__ void mbar_arrive_n(uint32_t bar, uint32_t n) {
    asm volatile("mbarrier.arrive.shared::cta.b64 _, [%0], %1;" :: "r"(bar), "r"(n) : "memory");
}
__device__ __forceinline__ bool mbar_try(uint32_t bar, uint32_t parity) {
    uint32_t ok;
    asm volatile("{\n.reg .pred p;\nmbarrier.try_wait.parity.shared::cta.b64 p, [%1], %2;\nselp.u32 %0, 1, 0, p;\n}"
                 : "=r"(ok) : "r"(bar), "r"(parity) : "memory");
    return ok != 0;
}
__device__ __forceinline__ bool mbar_test(uint32_t bar, uint32_t parity) {
    uint32_t ok;
    asm volatile("{\n.reg .pred p;\nmbarrier.test_wait.parity.shared::cta.b64 p, [%1], %2;\nselp.u32 %0, 1, 0, p;\n}"
                 : "=r"(ok) : "r"(bar), "r"(parity) : "memory");
    return ok != 0;
}
__device__ __forceinline__ void mbar_wait(uint32_t bar, uint32_t parity) {
    unsigned n = 0;
    while (!mbar_try(bar, parity)) { if (++n > SPIN_LIMIT) __trap(); }
}
constexpr unsigned long long POLICY_EVICT_FIRST = 0x12F0000000000000ull;
__device__ __forceinline__ void bulk_g2s(uint32_t dst, const void* src, uint32_t bytes, uint32_t bar) {
    asm volatile("cp.async.bulk.shared::cluster.global.mbarrier::complete_tx::bytes.L2::cache_hint [%0], [%1], %2, [%3], %4;"
                 :: "r"(dst), "l"(src), "r"(bytes), "r"(bar), "l"(POLICY_EVICT_FIRST) : "memory");
}
#define tma_2d_real tma_2d
__device__ __forceinline__ void tma_2d_real(uint32_t dst, const CUtensorMap* map, int c0, int c1, uint32_t bar) {
    asm volatile("cp.async.bulk.tensor.2d.shared::cluster.global.mbarrier::complete_tx::bytes [%0], [%1, {%3, %4}], [%2];"
                 :: "r"(dst), "l"(map), "r"(bar), "r"(c0), "r"(c1) : "memory");
}
__device__ __forceinline__ void bar_sync(int id, int n) { asm volatile("bar.sync %0, %1;" :: "r"(id), "r"(n) : "memory"); }
__device__ __forceinline__ void bar_arrive(int id, int n) { asm volatile("bar.arrive %0, %1;" :: "r"(id), "r"(n) : "memory"); }

__device__ __forceinline__ uint4 lds128(uint32_t a) {
    uint4 v; asm volatile("ld.shared.v4.u32 {%0,%1,%2,%3}, [%4];" : "=r"(v.x), "=r"(v.y), "=r"(v.z), "=r"(v.w) : "r"(a) : "memory"); return v;
}
__device__ __forceinline__ uint2 lds64(uint32_t a) {
    uint2 v; asm volatile("ld.shared.v2.u32 {%0,%1}, [%2];" : "=r"(v.x), "=r"(v.y) : "r"(a) : "memory"); return v;
}
__device__ __forceinline__ float lds32f(uint32_t a) {
    float v; asm volatile("ld.shared.f32 %0, [%1];" : "=f"(v) : "r"(a) : "memory"); return v;
}
__device__ __forceinline__ uint32_t lds32u(uint32_t a) {
    uint32_t v; asm volatile("ld.shared.u32 %0, [%1];" : "=r"(v) : "r"(a) : "memory"); return v;
}
__device__ __forceinline__ bool elect_one() {
    uint32_t p;
    asm volatile("{\n.reg .pred p;\nelect.sync _|p, 0xffffffff;\nselp.u32 %0, 1, 0, p;\n}" : "=r"(p));
    return p != 0;
}
__device__ __forceinline__ void sts128(uint32_t a, uint32_t x, uint32_t y, uint32_t z, uint32_t w) {
    asm volatile("st.shared.v4.u32 [%0], {%1,%2,%3,%4};" :: "r"(a), "r"(x), "r"(y), "r"(z), "r"(w) : "memory");
}
__device__ __forceinline__ void sts128f(uint32_t a, float x, float y, float z, float w) {
    asm volatile("st.shared.v4.f32 [%0], {%1,%2,%3,%4};" :: "r"(a), "f"(x), "f"(y), "f"(z), "f"(w) : "memory");
}
__device__ __forceinline__ void sts64(uint32_t a, uint32_t x, uint32_t y) {
    asm volatile("st.shared.v2.u32 [%0], {%1,%2};" :: "r"(a), "r"(x), "r"(y) : "memory");
}
__device__ __forceinline__ void sts64f(uint32_t a, float x, float y) {
    asm volatile("st.shared.v2.f32 [%0], {%1,%2};" :: "r"(a), "f"(x), "f"(y) : "memory");
}
__device__ __forceinline__ void sts32(uint32_t a, uint32_t x) {
    asm volatile("st.shared.u32 [%0], %1;" :: "r"(a), "r"(x) : "memory");
}
__device__ __forceinline__ void ldsm_x4_t(uint32_t a, uint32_t& r0, uint32_t& r1, uint32_t& r2, uint32_t& r3) {
    asm volatile("ldmatrix.sync.aligned.m8n8.x4.trans.shared.b16 {%0,%1,%2,%3}, [%4];"
                 : "=r"(r0), "=r"(r1), "=r"(r2), "=r"(r3) : "r"(a) : "memory");
}
__device__ __forceinline__ void mma16816(float (&c)[4], uint32_t a0, uint32_t a1, uint32_t a2, uint32_t a3,
                                         uint32_t b0, uint32_t b1) {
    asm volatile("mma.sync.aligned.m16n8k16.row.col.f32.bf16.bf16.f32 {%0,%1,%2,%3}, {%4,%5,%6,%7}, {%8,%9}, {%0,%1,%2,%3};"
                 : "+f"(c[0]), "+f"(c[1]), "+f"(c[2]), "+f"(c[3])
                 : "r"(a0), "r"(a1), "r"(a2), "r"(a3), "r"(b0), "r"(b1));
}
__device__ __forceinline__ uint32_t lo_pair(uint32_t a, uint32_t b) { return __byte_perm(a, b, 0x5410); }
__device__ __forceinline__ uint32_t hi_pair(uint32_t a, uint32_t b) { return __byte_perm(a, b, 0x7632); }
__device__ __forceinline__ float bf_lo(uint32_t v) { return __uint_as_float(v << 16); }
__device__ __forceinline__ float bf_hi(uint32_t v) { return __uint_as_float(v & 0xffff0000u); }
__device__ __forceinline__ float bf_round(float x) { return __bfloat162float(__float2bfloat16_rn(x)); }
__device__ __forceinline__ uint32_t pack_bf(float lo, float hi) {
    uint32_t r; asm("cvt.rn.bf16x2.f32 %0, %1, %2;" : "=r"(r) : "f"(hi), "f"(lo)); return r;
}
__device__ __forceinline__ uint2 ldg_nc64(const void* p) {
    uint2 v; asm volatile("ld.global.nc.L1::no_allocate.L2::128B.v2.u32 {%0,%1}, [%2];" : "=r"(v.x), "=r"(v.y) : "l"(p)); return v;
}
__device__ __forceinline__ uint32_t ldg_nc32(const void* p) {
    uint32_t v; asm volatile("ld.global.nc.L1::no_allocate.L2::128B.u32 %0, [%1];" : "=r"(v) : "l"(p)); return v;
}
__device__ __forceinline__ unsigned long long pkt(uint32_t payload, uint32_t tag) {
    return ((unsigned long long)tag << 32) | payload;
}
__device__ __forceinline__ void st_pkt(unsigned long long* p, unsigned long long v) {
    asm volatile("st.relaxed.gpu.global.u64 [%0], %1;" :: "l"(p), "l"(v) : "memory");
}
__device__ __forceinline__ void st_pkt2(unsigned long long* p, unsigned long long a, unsigned long long b) {
    asm volatile("st.relaxed.gpu.global.v2.u64 [%0], {%1,%2};" :: "l"(p), "l"(a), "l"(b) : "memory");
}
__device__ __forceinline__ unsigned long long ld_pkt(const unsigned long long* p) {
    unsigned long long v; asm volatile("ld.relaxed.gpu.global.u64 %0, [%1];" : "=l"(v) : "l"(p) : "memory"); return v;
}
__device__ __forceinline__ void ld_pkt2(const unsigned long long* p, unsigned long long& a, unsigned long long& b) {
    asm volatile("ld.relaxed.gpu.global.v2.u64 {%0,%1}, [%2];" : "=l"(a), "=l"(b) : "l"(p) : "memory");
}
__device__ __forceinline__ void st_v4(uint4* p, uint32_t a, uint32_t b, uint32_t c, uint32_t d) {
    asm volatile("st.relaxed.gpu.global.v4.u32 [%0], {%1,%2,%3,%4};" :: "l"(p), "r"(a), "r"(b), "r"(c), "r"(d) : "memory");
}
__device__ __forceinline__ uint4 ld_v4(const uint4* p) {
    uint4 v;
    asm volatile("ld.relaxed.gpu.global.v4.u32 {%0,%1,%2,%3}, [%4];" : "=r"(v.x), "=r"(v.y), "=r"(v.z), "=r"(v.w) : "l"(p) : "memory");
    return v;
}
__device__ __forceinline__ uint32_t hadd2_bf(uint32_t a, uint32_t b) {
    uint32_t r; asm("add.rn.bf16x2 %0, %1, %2;" : "=r"(r) : "r"(a), "r"(b)); return r;
}
__device__ __forceinline__ uint32_t tag_of(unsigned long long v) { return (uint32_t)(v >> 32); }
__device__ __forceinline__ uint32_t pay_of(unsigned long long v) { return (uint32_t)v; }

__device__ __forceinline__ unsigned long long to_fixed(float v) {
    const bool ok = fabsf(v) < 256.0f;
    const long long q = __float2ll_rn((ok ? v : 0.0f) * 0x1p50f);
    return ((unsigned long long)q & ~1023ull) | (ok ? 1u : 33u);
}
__device__ __forceinline__ float gelu_tanh(float x) {
    float u = 0.7978845608028654f * (x + 0.044715f * x * x * x);
    return 0.5f * x * (1.0f + tanhf(u));
}

#define LB_THREADS NTHREADS
__global__ void __launch_bounds__(LB_THREADS, 1)
fused_kernel(const __nv_bfloat16* __restrict__ x, const char* __restrict__ kc, const char* __restrict__ vc,
             const __nv_bfloat16* __restrict__ b1, const __nv_bfloat16* __restrict__ b2,
             const __nv_bfloat16* __restrict__ gw, __nv_bfloat16* __restrict__ out,
             const __grid_constant__ CUtensorMap map_wq, const __grid_constant__ CUtensorMap map_w1,
             const __grid_constant__ CUtensorMap map_wo, const __grid_constant__ CUtensorMap map_w2) {
    extern __shared__ unsigned char smem_raw[];
    uint32_t sb = ((uint32_t)__cvta_generic_to_shared(smem_raw) + 1023u) & ~1023u;
    asm volatile("" : "+r"(sb));
    const int tid = threadIdx.x, warp = tid >> 5, lane = tid & 31;
    const int c = blockIdx.x;
    const int hkv = c >> 4, b = (c >> 1) & 7, s = c & 1;
    const int rho = c >> 3, cg = c & 7;
    const int fs = rho * 7 + cg;
    const uint32_t bar_full = sb + OFF_BAR, bar_empty = bar_full + NS * 8, bar_w = bar_empty + NS * 8;

    if (warp == 8) {
        const size_t kv_off = ((size_t)(b * 8 + hkv) * SK + (SK - WIN) + s * 512) * ROW_BYTES;
        const char* src = kc + kv_off;
        const bool leader = elect_one();
        if (leader) {
#pragma unroll
            for (int i = 0; i < DEPTH_A; i++) mbar_init(bar_full + i * 8, 1);
            asm volatile("fence.mbarrier_init.release.cluster;" ::: "memory");
            mbar_expect_tx(bar_full, 224 * 64);
            tma_2d(sb + OFF_RING, &map_wq, 32 * c, 0, bar_full);
            mbar_expect_tx(bar_full + 8, 224 * 64);
            tma_2d(sb + OFF_RING + 224 * 64, &map_wq, 32 * c, 224, bar_full + 8);
#pragma unroll
            for (int i = POS_K; i < DEPTH_A; i++) {
                mbar_expect_tx(bar_full + i * 8, TILE_BYTES);
                bulk_g2s(sb + OFF_RING + i * TILE_BYTES, src + (i - POS_K) * TILE_BYTES, TILE_BYTES, bar_full + i * 8);
            }
#pragma unroll
            for (int i = DEPTH_A; i < NS; i++) mbar_init(bar_full + i * 8, 1);
#pragma unroll
            for (int i = 0; i < NS; i++) mbar_init(bar_empty + i * 8, 4);
#pragma unroll
            for (int i = 0; i < 7; i++) mbar_init(bar_w + i * 8, 1);
            asm volatile("fence.mbarrier_init.release.cluster;" ::: "memory");
        }
        __syncwarp();
        bar_arrive(2, NTHREADS);
        if (leader) {
            asm volatile("prefetch.tensormap [%0];" :: "l"(&map_w1) : "memory");
            asm volatile("prefetch.tensormap [%0];" :: "l"(&map_w2) : "memory");
            asm volatile("prefetch.tensormap [%0];" :: "l"(&map_wo) : "memory");
        }
        {
            int slot = DEPTH_A, ph = 1;
            int landed = 0, lslot = 0, lph = 0, depth = DEPTH_A;
            uint32_t due = (uint32_t)gtime32() + PACE_T0;
            auto acquire = [&](int pos) {
                while ((int)(gtime32() - due) < 0) { }
                due += (pos >= POS_W2 - 1) ? WPACE_NS : (pos >= POS_W2 - 1 - BURST_N) ? BURST_NS : PACE_NS;
                depth = (pos >= POS_W2) ? DEPTH_W : DEPTH_B;
                while (pos - landed >= depth && landed < POS_W2) {
                    mbar_wait(bar_full + lslot * 8, lph);
                    landed++;
                    if (++lslot == NS) { lslot = 0; lph ^= 1; }
                }
                if (pos >= NS) mbar_wait(bar_empty + slot * 8, ph);
            };
            src += (DEPTH_A - POS_K) * TILE_BYTES;
#pragma unroll 1
            for (int pos = DEPTH_A; pos < POS_W2; pos++) {
                acquire(pos);
                const uint32_t dst = sb + OFF_RING + slot * TILE_BYTES, bar = bar_full + slot * 8;
                if (pos == POS_GO && leader) mbar_arrive(bar_w + 32);
                if (pos == POS_W1) {
                    if (leader) {
                        if (cg < 7) {
                            mbar_expect_tx(bar, 448 * 32);
                            tma_2d(dst, &map_w1, 16 * fs, 0, bar);
                            tma_2d(dst + 224 * 32, &map_w1, 16 * fs, 224, bar);
                        } else {
                            mbar_arrive(bar);
                        }
                    }
                    src = vc + kv_off;
                } else {
                    if (leader) {
                        if (pos >= POS_W2 - 2) {
                            const uint32_t bar2 = bar_w + 40 + (pos - (POS_W2 - 2)) * 8;
                            mbar_expect_tx(bar, TILE_BYTES / 2);
                            mbar_expect_tx(bar2, TILE_BYTES / 2);
                            bulk_g2s(dst, src, TILE_BYTES / 2, bar);
                            bulk_g2s(dst + TILE_BYTES / 2, src + TILE_BYTES / 2, TILE_BYTES / 2, bar2);
                        } else
                        {
                            mbar_expect_tx(bar, TILE_BYTES);
                            bulk_g2s(dst, src, TILE_BYTES, bar);
                        }
                    }
                    src += TILE_BYTES;
                }
                if (++slot == NS) { slot = 0; ph ^= 1; }
            }
            if (cg == 7) return;
            due += PACE_WGAP;
            acquire(POS_W2);
            if (leader) {
                mbar_expect_tx(bar_w, 112 * 128);
                tma_2d(sb + OFF_RING + (POS_W2 % NS) * TILE_BYTES, &map_w2, 64 * cg, 112 * rho, bar_w);
            }
            if (++slot == NS) { slot = 0; ph ^= 1; }
            const uint32_t wdst = sb + OFF_RING + (POS_WO % NS) * TILE_BYTES;
            acquire(POS_WO);
            if (leader) {
                mbar_expect_tx(bar_w + 8, 4 * 4096);
#pragma unroll
                for (int i = 0; i < 4; i++) tma_2d(wdst + i * 4096, &map_wo, 64 * cg, 256 * rho + 32 * i, bar_w + 8);
            }
            if (++slot == NS) { slot = 0; ph ^= 1; }
            acquire(POS_WO + 1);
            if (leader) {
                mbar_expect_tx(bar_w + 16, 3 * 4096);
                mbar_expect_tx(bar_w + 24, 4096);
#pragma unroll
                for (int i = 4; i < 8; i++) tma_2d(wdst + i * 4096, &map_wo, 64 * cg, 256 * rho + 32 * i, bar_w + (i < 7 ? 16 : 24));
            }
        }
        return;
    }

    if (warp > 8) {
        const int mt = warp - 9;
        bar_sync(2, NTHREADS);
        if (cg == 7) return;
        mbar_wait(bar_w + 32, 0);
        const uint32_t tag = lds32u(sb + OFF_TG), par = tag & 1;
        const int ocol = 64 * cg + 16 * mt + (lane >> 2), ob = 2 * (lane & 3);
        unsigned long long* acc_p = &g_acc[(cg * 4 + mt) * 128 + lane];
        uint4* pbase = &g_pbuf[(cg * 4 + mt) * 512 + lane];
        __nv_bfloat16* out_p = out + ob * D_MODEL + ocol;
        asm volatile("" : "+l"(acc_p), "+l"(pbase), "+l"(out_p));
        auto bias_of = [&](int e) {
            return lds32f(sb + OFF_ST + (ob + (e & 1)) * 8 + 4) * __bfloat162float(b2[ocol + 8 * (e >> 1)]);
        };
        if (rho == 0) {
#pragma unroll
            for (int e = 0; e < 4; e++)
                asm volatile("red.relaxed.gpu.global.add.u64 [%0], %1;" :: "l"(acc_p + e * 32), "l"(to_fixed(bias_of(e))) : "memory");
        }
        uint32_t hf[7][2];
        {
            const unsigned long long* hsrc = &g_hbuf[(rho * 7 * 32 + lane) * 2];
            unsigned n = 0; bool ok;
            do {
                unsigned long long ha[7], hb[7];
#pragma unroll
                for (int i = 0; i < 7; i++) ld_pkt2(hsrc + i * 64, ha[i], hb[i]);
                ok = true;
#pragma unroll
                for (int i = 0; i < 7; i++) {
                    ok = ok && tag_of(ha[i]) == tag && tag_of(hb[i]) == tag;
                    hf[i][0] = pay_of(ha[i]); hf[i][1] = pay_of(hb[i]);
                }
                if (++n > SPIN_LIMIT) __trap();
            } while (!__all_sync(0xffffffffu, ok));
        }
        const uint32_t aoff = ((lane & 7) + ((lane >> 4) << 3)) * 128 + (((2 * mt + ((lane >> 3) & 1)) ^ (lane & 7)) << 4);
        float cc[4][4];
#pragma unroll
        for (int i = 0; i < 4; i++) { cc[i][0] = cc[i][1] = cc[i][2] = cc[i][3] = 0.f; }
        const unsigned long long* osrc = &g_obuf[((rho * 2 * 8 + 2 * mt) * 32 + lane) * 2];
        uint32_t os_l = sb + OFF_OS + lane * 16;
        asm volatile("" : "+l"(osrc), "+r"(os_l));
        unsigned long long pa[4], pb[4];
        mbar_wait(bar_w, 0);
        {
            const uint32_t wb = sb + OFF_RING + (POS_W2 % NS) * TILE_BYTES + aoff;
#pragma unroll
            for (int i = 0; i < 7; i++) {
                uint32_t a0, a1, a2, a3;
                ldsm_x4_t(wb + i * 2048, a0, a1, a2, a3);
                mma16816(cc[i & 3], a0, a1, a2, a3, hf[i][0], hf[i][1]);
            }
        }
        if (POLL_START) mbar_wait(bar_w + 8 * POLL_START, 0);
        ld_pkt2(osrc, pa[0], pb[0]);
        ld_pkt2(osrc + 512, pa[1], pb[1]);
        ld_pkt2(osrc + 64, pa[2], pb[2]);
        ld_pkt2(osrc + 512 + 64, pa[3], pb[3]);
        const int prow = 4 * ((lane & 7) >> 1) + (lane & 1) + ((((lane >> 4) ^ (lane >> 2)) & 1) << 1);
        uint32_t wb = sb + OFF_RING + (POS_WO % NS) * TILE_BYTES + prow * 128 + (((2 * mt + ((lane >> 3) & 1)) ^ (prow & 7)) << 4);
        asm volatile("" : "+r"(wb));
        uint32_t wf[16][4];
        auto load_w = [&](int lo, int hi) {
#pragma unroll
            for (int i = 0; i < 16; i++)
                if (i >= lo && i < hi) ldsm_x4_t(wb + i * 2048, wf[i][0], wf[i][1], wf[i][2], wf[i][3]);
        };
        mbar_wait(bar_w + 8, 0);
        load_w(0, 8);
        mbar_wait(bar_w + 16, 0);
        load_w(8, 14);
        const bool g2 = mbar_test(bar_w + 24, 0);
        if (g2) load_w(14, 16);
        unsigned n = 0;
        while (true) {
            bool okk[4];
#pragma unroll
            for (int i = 0; i < 4; i++) {
                asm volatile("" : "+l"(pa[i]), "+l"(pb[i]));
                okk[i] = (((uint32_t)pa[i] ^ par) & 1) == 0 && (((uint32_t)pb[i] ^ par) & 1) == 0;
            }
            const bool allok = __all_sync(0xffffffffu, okk[0] && okk[1] && okk[2] && okk[3]);
            if (allok) break;
            if (!okk[0]) ld_pkt2(osrc, pa[0], pb[0]);
            if (!okk[1]) ld_pkt2(osrc + 512, pa[1], pb[1]);
            if (!okk[2]) ld_pkt2(osrc + 64, pa[2], pb[2]);
            if (!okk[3]) ld_pkt2(osrc + 512 + 64, pa[3], pb[3]);
            if (++n > SPIN_LIMIT) __trap();
        }
#pragma unroll
        for (int i = 0; i < 2; i++) {
            sts128(os_l + mt * 1024 + i * 512,
                   hadd2_bf((uint32_t)pa[2 * i] & ~1u, (uint32_t)pa[2 * i + 1] & ~1u),
                   hadd2_bf((uint32_t)(pa[2 * i] >> 32), (uint32_t)(pa[2 * i + 1] >> 32)),
                   hadd2_bf((uint32_t)pb[2 * i] & ~1u, (uint32_t)pb[2 * i + 1] & ~1u),
                   hadd2_bf((uint32_t)(pb[2 * i] >> 32), (uint32_t)(pb[2 * i + 1] >> 32)));
        }
        bar_sync(4, 128);
        TSR(7);
        uint4 of[8];
#pragma unroll
        for (int i = 0; i < 6; i++) of[i] = lds128(os_l + i * 512);
        auto mm = [&](int lo, int hi) {
#pragma unroll
            for (int i = 0; i < 16; i++)
                if (i >= lo && i < hi)
                    mma16816(cc[i & 3], wf[i][0], wf[i][1], wf[i][2], wf[i][3],
                             (i & 1) ? of[i >> 1].z : of[i >> 1].x, (i & 1) ? of[i >> 1].w : of[i >> 1].y);
        };
        mm(0, 4);
        of[6] = lds128(os_l + 6 * 512);
        of[7] = lds128(os_l + 7 * 512);
        mm(4, 14);
        if (!g2) { mbar_wait(bar_w + 24, 0); load_w(14, 16); }
        mm(14, 16);
        float res[4];
        unsigned long long tot[4], add[4];
#pragma unroll
        for (int e = 0; e < 4; e++) {
            res[e] = (cc[0][e] + cc[1][e]) + (cc[2][e] + cc[3][e]);
            add[e] = to_fixed(res[e]);
            asm volatile("atom.relaxed.gpu.global.add.u64 %0, [%1], %2;" : "=l"(tot[e]) : "l"(acc_p + e * 32), "l"(add[e]) : "memory");
        }
        TSR(8);
        st_v4(pbase + rho * 32, (__float_as_uint(res[0]) & ~1u) | par, (__float_as_uint(res[1]) & ~1u) | par,
                                (__float_as_uint(res[2]) & ~1u) | par, (__float_as_uint(res[3]) & ~1u) | par);
        uint32_t slow = 0;
#pragma unroll
        for (int e = 0; e < 4; e++) {
            tot[e] += add[e];
            const bool last = ((uint32_t)tot[e] & 31) == 17;
            const float val = (float)(long long)tot[e] * 0x1p-50f;
            const bool good = ((uint32_t)tot[e] & 0x3e0) == 0 && fabsf(val) >= 0x1p-24f;
            const __nv_bfloat16 r = __float2bfloat16_rn(val);
            if (last && good)
                asm volatile("st.global.u16 [%0], %1;" :: "l"(out_p + (e & 1) * D_MODEL + 8 * (e >> 1)), "h"(__bfloat16_as_ushort(r)) : "memory");
            if (last) asm volatile("st.relaxed.gpu.global.u64 [%0], %1;" :: "l"(acc_p + e * 32), "l"(0ull) : "memory");
            if (last && !good) slow |= 1u << e;
            if (e == 0 && last && cg == 0 && tid == 288)
                asm volatile("st.relaxed.gpu.global.u32 [%0], %1;" :: "l"(&g_epoch), "r"(tag) : "memory");
        }
        if (slow) {
#pragma unroll 1
            for (int e = 0; e < 4; e++) {
                if (!((slow >> e) & 1)) continue;
                float r = bias_of(e);
#pragma unroll 1
                for (int src = 0; src < 16; src++) {
                    const uint32_t* q = reinterpret_cast<const uint32_t*>(pbase + src * 32) + e;
                    uint32_t u; unsigned m = 0;
                    do {
                        asm volatile("ld.relaxed.gpu.global.u32 %0, [%1];" : "=r"(u) : "l"(q) : "memory");
                        if (++m > SPIN_LIMIT) __trap();
                    } while ((u & 1) != par);
                    r += __uint_as_float(u & ~1u);
                }
                out_p[(e & 1) * D_MODEL + 8 * (e >> 1)] = __float2bfloat16_rn(r);
            }
        }
        return;
    }

    const int g = lane >> 2, t = lane & 3;
    uint32_t epoch;
    asm volatile("ld.relaxed.gpu.global.u32 %0, [%1];" : "=r"(epoch) : "l"(&g_epoch) : "memory");
    unsigned long long* const qdst = &g_qbuf[(hkv * 8 + ((tid >> 4) & 7)) * 256 + (c & 15) * 16 + (tid & 15)];
    if (tid < 128) st_pkt(qdst, 0ull);
    uint32_t b1v = 0;
    if (cg < 7) b1v = *reinterpret_cast<const uint32_t*>(b1 + 16 * fs + 2 * (((tid >> 1) & 3) + 4 * (tid & 1)));

    {
        uint32_t xr[7], gr[7];
#pragma unroll
        for (int i = 0; i < 7; i++) {
            xr[i] = *reinterpret_cast<const uint32_t*>(x + warp * D_MODEL + 2 * (lane + 32 * i));
            gr[i] = *reinterpret_cast<const uint32_t*>(gw + 2 * (lane + 32 * i));
        }
        float sum = 0.f, gz = 0.f;
#pragma unroll
        for (int i = 0; i < 7; i++) {
            sts32(sb + OFF_XS + warp * XS_PITCH + (lane + 32 * i) * 4, xr[i]);
            sum += bf_lo(xr[i]) + bf_hi(xr[i]);
            gz += bf_round(bf_lo(xr[i]) * bf_lo(gr[i])) + bf_round(bf_hi(xr[i]) * bf_hi(gr[i]));
        }
#pragma unroll
        for (int o = 16; o; o >>= 1) { sum += __shfl_xor_sync(0xffffffffu, sum, o); gz += __shfl_xor_sync(0xffffffffu, gz, o); }
        const float mean = sum * (1.0f / D_MODEL);
        float var = 0.f;
#pragma unroll
        for (int i = 0; i < 7; i++) {
            const float d0 = bf_lo(xr[i]) - mean, d1 = bf_hi(xr[i]) - mean;
            var += d0 * d0 + d1 * d1;
        }
#pragma unroll
        for (int o = 16; o; o >>= 1) var += __shfl_xor_sync(0xffffffffu, var, o);
        const float den = bf_round(sqrtf(bf_round(bf_round(var * (1.0f / D_MODEL)) + 1e-5f)));
        const float mb = bf_round(mean);
#pragma unroll
        for (int i = 0; i < 7; i++) {
            sts32(sb + OFF_YS + warp * XS_PITCH + (lane + 32 * i) * 4,
                  pack_bf(__fdividef(bf_round(bf_lo(xr[i]) - mb), den), __fdividef(bf_round(bf_hi(xr[i]) - mb), den)));
        }
        if (lane == 0) {
            const float gt = bf_round(__fdividef(1.0f, 1.0f + __expf(-bf_round(gz))));
            sts64f(sb + OFF_ST + warp * 8, gt, bf_round(1.0f - gt));
        }
    }
    const uint32_t tag = (epoch + 1) ? epoch + 1 : 2;
    if (tid == 0) sts32(sb + OFF_TG, tag);
    bar_sync(2, NTHREADS);
    TSR(0);
    {
        const int mt = warp & 1, kq = warp >> 1;
        const int row = 112 * kq + (lane & 7) + ((lane >> 4) << 3);
        const uint32_t wa = sb + OFF_RING + row * 64 + (((2 * mt + ((lane >> 3) & 1)) ^ ((row >> 1) & 3)) << 4);
        const uint32_t xa = sb + OFF_XS + g * XS_PITCH + (112 * kq + 2 * t) * 2;
        uint32_t xb[7][2];
#pragma unroll
        for (int ks = 0; ks < 7; ks++) { xb[ks][0] = lds32u(xa + ks * 32); xb[ks][1] = lds32u(xa + ks * 32 + 16); }
        mbar_wait(bar_full + (kq >> 1) * 8, 0);
        float c0[4] = {0.f, 0.f, 0.f, 0.f}, c1[4] = {0.f, 0.f, 0.f, 0.f};
#pragma unroll
        for (int ks = 0; ks < 7; ks++) {
            uint32_t a0, a1, a2, a3;
            ldsm_x4_t(wa + ks * 1024, a0, a1, a2, a3);
            if (ks & 1) mma16816(c1, a0, a1, a2, a3, xb[ks][0], xb[ks][1]);
            else mma16816(c0, a0, a1, a2, a3, xb[ks][0], xb[ks][1]);
        }
        sts128f(sb + OFF_U + warp * 512 + lane * 16, c0[0] + c1[0], c0[1] + c1[1], c0[2] + c1[2], c0[3] + c1[3]);
        bar_sync(1, 256);
        if (tid < 128) {
            const int pb = tid >> 4, p = tid & 15;
            const uint32_t ra = sb + OFF_U + (p >> 3) * 512 + (4 * ((2 * p) & 7) + (pb >> 1)) * 16 + ((p >> 2) & 1) * 8 + (pb & 1) * 4;
            float v0 = 0.f, v1 = 0.f;
#pragma unroll
            for (int w = 0; w < 4; w++) { v0 += lds32f(ra + w * 1024); v1 += lds32f(ra + w * 1024 + 64); }
            st_pkt(qdst, pkt(pack_bf(v0, v1), tag));
        } else if (tid == 128) {
            mbar_arrive_n(bar_empty, 4);
            mbar_arrive_n(bar_empty + 8, 4);
        }
    }
    TSR(1);
    {
        const unsigned long long* src = &g_qbuf[(hkv * 8 + b) * 256 + tid];
        unsigned long long v;
        unsigned n = 0;
        do { v = ld_pkt(src); if (++n > SPIN_LIMIT) __trap(); } while (tag_of(v) != tag);
        sts32(sb + OFF_QS + tid * 4, pay_of(v));
    }
    bar_sync(1, 256);
    TSR(2);

    int slot = POS_K + (warp >> 2), ph = 0;
    {
        const int j8 = lane & 7;
        float qr[2][4][8];
#pragma unroll
        for (int h = 0; h < 2; h++)
#pragma unroll
            for (int i = 0; i < 4; i++) {
                const uint4 u = lds128(sb + OFF_QS + h * 512 + i * 128 + j8 * 16);
                qr[h][i][0] = bf_lo(u.x); qr[h][i][1] = bf_hi(u.x); qr[h][i][2] = bf_lo(u.y); qr[h][i][3] = bf_hi(u.y);
                qr[h][i][4] = bf_lo(u.z); qr[h][i][5] = bf_hi(u.z); qr[h][i][6] = bf_lo(u.w); qr[h][i][7] = bf_hi(u.w);
            }
        const uint32_t koff = (8 * (warp & 3) + (lane >> 3)) * ROW_BYTES + j8 * 16;
        const uint32_t soff = sb + OFF_U + (8 * warp + 4 * (j8 >> 2) + (lane >> 3)) * 8 + ((j8 >> 1) & 1) * 4;
#pragma unroll 1
        for (int it = 0; it < 8; it++) {
            mbar_wait(bar_full + slot * 8, ph);
            const uint32_t base = sb + OFF_RING + slot * TILE_BYTES + koff;
            uint4 la[4], lb[4];
#pragma unroll
            for (int i = 0; i < 4; i++) { la[i] = lds128(base + i * 128); lb[i] = lds128(base + 4 * ROW_BYTES + i * 128); }
            float a0 = 0.f, a1 = 0.f, b0 = 0.f, b1_ = 0.f;
#pragma unroll
            for (int i = 0; i < 4; i++) {
                const uint32_t wa[4] = {la[i].x, la[i].y, la[i].z, la[i].w}, wb[4] = {lb[i].x, lb[i].y, lb[i].z, lb[i].w};
#pragma unroll
                for (int e = 0; e < 4; e++) {
                    const float al = bf_lo(wa[e]), ah = bf_hi(wa[e]), bl = bf_lo(wb[e]), bh = bf_hi(wb[e]);
                    a0 = fmaf(al, qr[0][i][2 * e], a0); a1 = fmaf(al, qr[1][i][2 * e], a1);
                    b0 = fmaf(bl, qr[0][i][2 * e], b0); b1_ = fmaf(bl, qr[1][i][2 * e], b1_);
                    a0 = fmaf(ah, qr[0][i][2 * e + 1], a0); a1 = fmaf(ah, qr[1][i][2 * e + 1], a1);
                    b0 = fmaf(bh, qr[0][i][2 * e + 1], b0); b1_ = fmaf(bh, qr[1][i][2 * e + 1], b1_);
                }
            }
            __syncwarp();
            if (lane == 0) mbar_arrive(bar_empty + slot * 8);
            const bool up = j8 & 4;
            float k0 = (up ? b0 : a0) + __shfl_xor_sync(0xffffffffu, up ? a0 : b0, 4);
            float k1 = (up ? b1_ : a1) + __shfl_xor_sync(0xffffffffu, up ? a1 : b1_, 4);
            const bool up2 = j8 & 2;
            float r = (up2 ? k1 : k0) + __shfl_xor_sync(0xffffffffu, up2 ? k0 : k1, 2);
            r += __shfl_xor_sync(0xffffffffu, r, 1);
            if ((lane & 1) == 0) sts32(soff + it * 512, __float_as_uint(r));
            slot += 2; if (slot >= NS) { slot -= NS; ph ^= 1; }
        }
        slot += 1; if (slot >= NS) { slot -= NS; ph ^= 1; }
    }
    if (warp < 4 && cg < 7) {
        const int row = 112 * warp + (lane & 7) + ((lane >> 4) << 3);
        const uint32_t wa = sb + OFF_RING + (POS_W1 % NS) * TILE_BYTES + row * 32 + ((((lane >> 3) & 1) ^ ((row >> 2) & 1)) << 4);
        const uint32_t ya = sb + OFF_YS + g * XS_PITCH + (112 * warp + 2 * t) * 2;
        mbar_wait(bar_full + (POS_W1 % NS) * 8, (POS_W1 / NS) & 1);
        float c0[4] = {0.f, 0.f, 0.f, 0.f};
#pragma unroll
        for (int ks = 0; ks < 7; ks++) {
            uint32_t a0, a1, a2, a3;
            ldsm_x4_t(wa + ks * 512, a0, a1, a2, a3);
            mma16816(c0, a0, a1, a2, a3, lds32u(ya + ks * 32), lds32u(ya + ks * 32 + 16));
        }
        sts128f(sb + OFF_HR + warp * 512 + lane * 16, c0[0], c0[1], c0[2], c0[3]);
    }
    bar_sync(1, 256);
    TSR(3);
    if (tid == 255) mbar_arrive_n(bar_empty + (POS_W1 % NS) * 8, 4);
    float own_m, own_l;
    {
        const uint4 p0 = lds128(sb + OFF_U + tid * 16);
        const float s00 = bf_round(__uint_as_float(p0.x)) * 0.0625f;
        const float s01 = bf_round(__uint_as_float(p0.y)) * 0.0625f;
        const float s10 = bf_round(__uint_as_float(p0.z)) * 0.0625f;
        const float s11 = bf_round(__uint_as_float(p0.w)) * 0.0625f;
        float m0 = fmaxf(s00, s10), m1 = fmaxf(s01, s11);
#pragma unroll
        for (int o = 16; o; o >>= 1) {
            m0 = fmaxf(m0, __shfl_xor_sync(0xffffffffu, m0, o));
            m1 = fmaxf(m1, __shfl_xor_sync(0xffffffffu, m1, o));
        }
        if (lane == 0) sts64f(sb + OFF_WM + warp * 8, m0, m1);
        if (tid < 64 && cg < 7) {
            const int L = tid >> 1, hf = tid & 1, pb = L >> 2;
            const uint32_t ra = sb + OFF_HR + (4 * (2 * (L & 3)) + (pb >> 1)) * 16 + hf * 8 + (pb & 1) * 4;
            float v0 = 0.f, v1 = 0.f;
#pragma unroll
            for (int w = 0; w < 4; w++) { v0 += lds32f(ra + w * 512); v1 += lds32f(ra + w * 512 + 64); }
            const float omg = lds32f(sb + OFF_ST + pb * 8 + 4);
            v0 = bf_round(gelu_tanh(bf_round(bf_round(v0) + bf_lo(b1v)))) * omg;
            v1 = bf_round(gelu_tanh(bf_round(bf_round(v1) + bf_hi(b1v)))) * omg;
            st_pkt(&g_hbuf[(fs * 32 + L) * 2 + hf], pkt(pack_bf(v0, v1), tag));
        }
        bar_sync(1, 256);
#pragma unroll
        for (int w = 0; w < 4; w++) {
            const uint4 v = lds128(sb + OFF_WM + w * 16);
            m0 = fmaxf(m0, fmaxf(__uint_as_float(v.x), __uint_as_float(v.z)));
            m1 = fmaxf(m1, fmaxf(__uint_as_float(v.y), __uint_as_float(v.w)));
        }
        const float e00 = __expf(s00 - m0), e10 = __expf(s10 - m0), e01 = __expf(s01 - m1), e11 = __expf(s11 - m1);
        {
            const uint32_t pa = sb + OFF_PS + (tid >> 4) * 256 + (tid & 1) * 128 + ((tid >> 1) & 7) * 8;
            sts64f(pa, e00, e01);
            sts64f(pa + 64, e10, e11);
        }
        float l0 = e00 + e10, l1 = e01 + e11;
#pragma unroll
        for (int o = 16; o; o >>= 1) { l0 += __shfl_xor_sync(0xffffffffu, l0, o); l1 += __shfl_xor_sync(0xffffffffu, l1, o); }
        if (lane == 0) sts64f(sb + OFF_WS + warp * 8, l0, l1);
        bar_sync(1, 256);
        const int hh = lane >> 4;
        float l = 0.f;
#pragma unroll
        for (int w = 0; w < 8; w++) l += lds32f(sb + OFF_WS + w * 8 + hh * 4);
        own_m = hh ? m1 : m0; own_l = l;
        if ((tid & ~16) == 0)
            st_pkt2(&g_mlbuf[c * 4 + hh * 2], pkt(__float_as_uint(own_m), tag), pkt(__float_as_uint(l), tag));
    }
    TSR(4);
    float acc[2][8];
#pragma unroll
    for (int i = 0; i < 8; i++) { acc[0][i] = acc[1][i] = 0.f; }
    const int r4 = lane >> 3, j8 = lane & 7, dq = warp & 3;
    const unsigned long long* msrc = &g_mlbuf[(c ^ 1) * 4 + (lane >> 4) * 2];
    unsigned long long pm = 0, pl = 0;
    float scale = 0.f;
    unsigned long long* const odst =
        &g_obuf[((((2 * hkv + (r4 >> 1)) * 2 + s) * 8 + 2 * dq + (j8 >> 2)) * 32 + b * 4 + 2 * (j8 & 1) + (r4 & 1)) * 2 + ((j8 >> 1) & 1)];
    {
        const uint32_t poff = sb + OFF_PS + (warp >> 2) * 256 + r4 * 64;
        const uint32_t voff = r4 * ROW_BYTES + dq * 128 + j8 * 16;
        auto rows = [&](const uint4 (&r)[4], const uint4& pa, const uint4& pb) {
#pragma unroll
            for (int j = 0; j < 4; j++) {
                const uint4& pp = (j & 2) ? pb : pa;
                const float p0 = __uint_as_float((j & 1) ? pp.z : pp.x), p1 = __uint_as_float((j & 1) ? pp.w : pp.y);
                const uint32_t wv[4] = {r[j].x, r[j].y, r[j].z, r[j].w};
#pragma unroll
                for (int e = 0; e < 4; e++) {
                    const float lo = bf_lo(wv[e]), hi = bf_hi(wv[e]);
                    acc[0][2 * e] = fmaf(lo, p0, acc[0][2 * e]); acc[1][2 * e] = fmaf(lo, p1, acc[1][2 * e]);
                    acc[0][2 * e + 1] = fmaf(hi, p0, acc[0][2 * e + 1]); acc[1][2 * e + 1] = fmaf(hi, p1, acc[1][2 * e + 1]);
                }
            }
        };
#pragma unroll 1
        for (int i = 0; i < 8; i++) {
            uint4 pf[4];
#pragma unroll
            for (int j = 0; j < 4; j++) pf[j] = lds128(poff + i * 512 + j * 16);
            if (i == PRE_IT && warp >= 4) {
                ld_pkt2(msrc, pm, pl);
                st_pkt(odst, (unsigned long long)((tag & 1) ^ 1));
            }
            if (i == PRE_IT + 3 && warp >= 4) {
                unsigned n = 0;
                while (tag_of(pm) != tag || tag_of(pl) != tag) { ld_pkt2(msrc, pm, pl); if (++n > SPIN_LIMIT) __trap(); }
                const float m_o = __uint_as_float(pay_of(pm)), l_o = __uint_as_float(pay_of(pl));
                const float m = fmaxf(own_m, m_o);
                const float e_s = __expf(own_m - m), e_o = __expf(m_o - m);
                scale = __fdividef(lds32f(sb + OFF_ST + b * 8) * e_s, e_s * own_l + e_o * l_o);
                __syncwarp();
            }
            mbar_wait(bar_full + slot * 8, ph);
            const uint32_t base = sb + OFF_RING + slot * TILE_BYTES + voff;
            uint4 ra[4], rb[4];
#pragma unroll
            for (int j = 0; j < 4; j++) ra[j] = lds128(base + j * 4 * ROW_BYTES);
            if (i == 7) {
                rows(ra, pf[0], pf[1]);
                mbar_wait(bar_w + 40 + (warp >> 2) * 8, 0);
#pragma unroll
                for (int j = 0; j < 4; j++) rb[j] = lds128(base + (j + 4) * 4 * ROW_BYTES);
                rows(rb, pf[2], pf[3]);
                break;
            }
#pragma unroll
            for (int j = 0; j < 4; j++) rb[j] = lds128(base + (j + 4) * 4 * ROW_BYTES);
            rows(ra, pf[0], pf[1]);
            rows(rb, pf[2], pf[3]);
            __syncwarp();
            if (lane == 0) mbar_arrive(bar_empty + slot * 8);
            slot += 2; if (slot >= NS) { slot -= NS; ph ^= 1; }
        }
    }
    TSR(5);
    {
        const bool up = lane & 16, up2 = lane & 8;
        float u[8], v[4];
#pragma unroll
        for (int e = 0; e < 8; e++) u[e] = (up ? acc[1][e] : acc[0][e]) + __shfl_xor_sync(0xffffffffu, up ? acc[0][e] : acc[1][e], 16);
#pragma unroll
        for (int e = 0; e < 4; e++) v[e] = (up2 ? u[e + 4] : u[e]) + __shfl_xor_sync(0xffffffffu, up2 ? u[e] : u[e + 4], 8);
        const uint32_t xa = sb + OFF_U + dq * 512 + lane * 16;
        if (warp < 4) {
            sts128f(xa, v[0], v[1], v[2], v[3]);
            bar_arrive(5 + dq, 64);
        } else {
            bar_sync(5 + dq, 64);
            const uint4 o = lds128(xa);
            const float x0 = (v[0] + __uint_as_float(o.x)) * scale, x1 = (v[1] + __uint_as_float(o.y)) * scale;
            const float x2 = (v[2] + __uint_as_float(o.z)) * scale, x3 = (v[3] + __uint_as_float(o.w)) * scale;
            const bool sw = j8 & 1;
            const float v0 = sw ? x2 : x0, v1 = sw ? x3 : x1, v2 = sw ? x0 : x2, v3 = sw ? x1 : x3;
            const uint32_t w0 = (pack_bf(v0, v1) & 0xffff0000u) | (((__float_as_uint(v0) + 0x10000u) >> 16) & 0xfffeu) | (tag & 1);
            st_pkt(odst, pkt(w0, pack_bf(v2, v3)));
        }
    }
}

typedef CUresult (*EncodeFn)(CUtensorMap*, CUtensorMapDataType, cuuint32_t, void*, const cuuint64_t*, const cuuint64_t*,
                             const cuuint32_t*, const cuuint32_t*, CUtensorMapInterleave, CUtensorMapSwizzle,
                             CUtensorMapL2promotion, CUtensorMapFloatOOBfill);

bool make_map(EncodeFn fn, CUtensorMap* m, const void* ptr, int cols, int rows, int box_cols, int box_rows,
              CUtensorMapSwizzle swz) {
    cuuint64_t dims[2] = {(cuuint64_t)cols, (cuuint64_t)rows};
    cuuint64_t strides[1] = {(cuuint64_t)cols * 2};
    cuuint32_t box[2] = {(cuuint32_t)box_cols, (cuuint32_t)box_rows};
    cuuint32_t es[2] = {1, 1};
    return fn(m, CU_TENSOR_MAP_DATA_TYPE_BFLOAT16, 2, const_cast<void*>(ptr), dims, strides, box, es,
              CU_TENSOR_MAP_INTERLEAVE_NONE, swz, CU_TENSOR_MAP_L2_PROMOTION_L2_128B,
              CU_TENSOR_MAP_FLOAT_OOB_FILL_NONE) == CUDA_SUCCESS;
}

}

extern "C" void kernel_launch(void* const* d_in, const int* in_sizes, int n_in, void* d_out, int out_size) {
    (void)in_sizes; (void)n_in; (void)out_size;
    static EncodeFn enc = nullptr;
    if (!enc) {
        void* fn = nullptr;
        cudaDriverEntryPointQueryResult qr;
        cudaGetDriverEntryPoint("cuTensorMapEncodeTiled", &fn, cudaEnableDefault, &qr);
        enc = (EncodeFn)fn;
        cudaFuncSetAttribute(fused_kernel, cudaFuncAttributeMaxDynamicSharedMemorySize, SMEM_BYTES);
    }
    CUtensorMap map_wq, map_w1, map_wo, map_w2;
    make_map(enc, &map_wq, d_in[3], N_QCOL, D_MODEL, 32, 224, CU_TENSOR_MAP_SWIZZLE_64B);
    make_map(enc, &map_w1, d_in[6], FF, D_MODEL, 16, 224, CU_TENSOR_MAP_SWIZZLE_32B);
    make_map(enc, &map_wo, d_in[4], D_MODEL, N_QCOL, 64, 32, CU_TENSOR_MAP_SWIZZLE_128B);
    make_map(enc, &map_w2, d_in[8], D_MODEL, FF, 64, 112, CU_TENSOR_MAP_SWIZZLE_128B);

    cudaLaunchConfig_t cfg = {};
    cfg.gridDim = dim3(NCTA);
    cfg.blockDim = dim3(LB_THREADS);
    cfg.dynamicSmemBytes = SMEM_BYTES;
    cfg.stream = cudaStreamPerThread;
    cudaLaunchAttribute at[1];
    at[0].id = cudaLaunchAttributeCooperative;
    at[0].val.cooperative = 1;
    cfg.attrs = at;
    cfg.numAttrs = 1;
    cudaLaunchKernelEx(&cfg, fused_kernel,
                       (const __nv_bfloat16*)d_in[0], (const char*)d_in[1], (const char*)d_in[2],
                       (const __nv_bfloat16*)d_in[7], (const __nv_bfloat16*)d_in[9],
                       (const __nv_bfloat16*)d_in[10], (__nv_bfloat16*)d_out, map_wq, map_w1, map_wo, map_w2);
}
```

```cpp
#include <cuda_runtime.h>
#include <cuda_bf16.h>
#include <cuda.h>
#include <stdint.h>

namespace {

constexpr int D_MODEL = 448;
constexpr int N_QCOL = 4096;
constexpr int SK = 4096;
constexpr int WIN = 1024;
constexpr int FF = 1792;
constexpr int NCTA = 128;
constexpr int NTHREADS = 416;

constexpr int ROW_BYTES = 512;
constexpr int TILE_ROWS = 32;
constexpr int TILE_BYTES = TILE_ROWS * ROW_BYTES;
constexpr int NS = 12;
constexpr int NT = 512 / TILE_ROWS;
constexpr int POS_K = 2, POS_W1 = POS_K + NT, POS_V = POS_W1 + 1, POS_W2 = POS_V + NT, POS_WO = POS_W2 + 1;
static_assert(POS_WO % NS + 2 <= NS, "wo tile must not wrap");
constexpr int POS_GO = POS_V + 6;

constexpr int POS_FIRST = 3;
constexpr int PACE_T0 = 650;
constexpr int PACE_NS = 648;
constexpr int PACE_WGAP = 800;
constexpr int PACE_W = 450;
constexpr int DEPTH_LO = 2;
constexpr int DEPTH_HI = 10;
constexpr int DEPTH_W = 3;
constexpr int QPOLL_T = 4000;
constexpr int PRE_IT = 3;

constexpr int XS_PITCH = 912;

constexpr int OFF_RING = 0;
constexpr int OFF_U = NS * TILE_BYTES;
constexpr int OFF_XS = OFF_U + 8192;
constexpr int OFF_YS = OFF_U + 16384;
constexpr int OFF_OS = OFF_YS;
constexpr int OFF_PS = OFF_YS + 8192;
constexpr int OFF_QS = OFF_PS + 4096;
constexpr int OFF_HR = OFF_QS + 1024;
constexpr int OFF_ST = OFF_HR + 2048;
constexpr int OFF_WM = OFF_ST + 64;
constexpr int OFF_WS = OFF_WM + 64;
constexpr int OFF_TG = OFF_WS + 64;
constexpr int OFF_BAR = OFF_TG + 16;
constexpr int B_W2 = 0, B_WO0 = 8, B_WO1 = 16, B_WO2 = 24, B_GO = 32, B_VLAST = 40  , B_OS = 56;
constexpr int NBAR = 2 * NS + 8;
constexpr int SMEM_BYTES = OFF_BAR + NBAR * 8 + 1024;

constexpr unsigned SPIN_LIMIT = 1u << 22;

__device__ unsigned g_epoch;
__device__ __align__(128) unsigned long long g_qbuf[8 * 8 * 256];
__device__ __align__(128) unsigned long long g_hbuf[16 * 7 * 32 * 2];
__device__ __align__(128) unsigned long long g_mlbuf[NCTA * 4];
__device__ __align__(128) unsigned long long g_obuf[16 * 2 * 8 * 32 * 2];
__device__ __align__(128) uint4 g_pbuf[7 * 4 * 16 * 32];
__device__ __align__(128) unsigned long long g_acc[7 * 4 * 4 * 32];

__device__ __forceinline__ uint32_t gtime32() { uint32_t t; asm volatile("mov.u32 %0, %globaltimer_lo;" : "=r"(t)); return t; }
__device__ __forceinline__ void mbar_init(uint32_t bar, int cnt) {
    asm volatile("mbarrier.init.shared::cta.b64 [%0], %1;" :: "r"(bar), "r"(cnt) : "memory");
}
__device__ __forceinline__ void mbar_expect_tx(uint32_t bar, uint32_t bytes) {
    asm volatile("mbarrier.arrive.expect_tx.shared::cta.b64 _, [%0], %1;" :: "r"(bar), "r"(bytes) : "memory");
}
__device__ __forceinline__ void mbar_arrive(uint32_t bar) {
    asm volatile("mbarrier.arrive.shared::cta.b64 _, [%0];" :: "r"(bar) : "memory");
}
__device__ __forceinline__ void mbar_arrive_n(uint32_t bar, uint32_t n) {
    asm volatile("mbarrier.arrive.shared::cta.b64 _, [%0], %1;" :: "r"(bar), "r"(n) : "memory");
}
__device__ __forceinline__ bool mbar_try(uint32_t bar, uint32_t parity) {
    uint32_t ok;
    asm volatile("{\n.reg .pred p;\nmbarrier.try_wait.parity.shared::cta.b64 p, [%1], %2;\nselp.u32 %0, 1, 0, p;\n}"
                 : "=r"(ok) : "r"(bar), "r"(parity) : "memory");
    return ok != 0;
}
__device__ __forceinline__ bool mbar_test(uint32_t bar, uint32_t parity) {
    uint32_t ok;
    asm volatile("{\n.reg .pred p;\nmbarrier.test_wait.parity.shared::cta.b64 p, [%1], %2;\nselp.u32 %0, 1, 0, p;\n}"
                 : "=r"(ok) : "r"(bar), "r"(parity) : "memory");
    return ok != 0;
}
__device__ __forceinline__ void mbar_wait(uint32_t bar, uint32_t parity) {
    unsigned n = 0;
    while (!mbar_try(bar, parity)) { if (++n > SPIN_LIMIT) __trap(); }
}
constexpr unsigned long long POLICY_EVICT_FIRST = 0x12F0000000000000ull;
__device__ __forceinline__ void bulk_g2s(uint32_t dst, const void* src, uint32_t bytes, uint32_t bar) {
    asm volatile("cp.async.bulk.shared::cluster.global.mbarrier::complete_tx::bytes.L2::cache_hint [%0], [%1], %2, [%3], %4;"
                 :: "r"(dst), "l"(src), "r"(bytes), "r"(bar), "l"(POLICY_EVICT_FIRST) : "memory");
}
__device__ __forceinline__ void tma_2d(uint32_t dst, const CUtensorMap* map, int c0, int c1, uint32_t bar) {
    asm volatile("cp.async.bulk.tensor.2d.shared::cluster.global.mbarrier::complete_tx::bytes [%0], [%1, {%3, %4}], [%2];"
                 :: "r"(dst), "l"(map), "r"(bar), "r"(c0), "r"(c1) : "memory");
}
__device__ __forceinline__ void bar_sync(int id, int n) { asm volatile("bar.sync %0, %1;" :: "r"(id), "r"(n) : "memory"); }
__device__ __forceinline__ void bar_arrive(int id, int n) { asm volatile("bar.arrive %0, %1;" :: "r"(id), "r"(n) : "memory"); }
__device__ __forceinline__ bool elect_one() {
    uint32_t p;
    asm volatile("{\n.reg .pred p;\nelect.sync _|p, 0xffffffff;\nselp.u32 %0, 1, 0, p;\n}" : "=r"(p));
    return p != 0;
}
__device__ __forceinline__ uint4 lds128(uint32_t a) {
    uint4 v; asm volatile("ld.shared.v4.u32 {%0,%1,%2,%3}, [%4];" : "=r"(v.x), "=r"(v.y), "=r"(v.z), "=r"(v.w) : "r"(a) : "memory"); return v;
}
__device__ __forceinline__ float lds32f(uint32_t a) {
    float v; asm volatile("ld.shared.f32 %0, [%1];" : "=f"(v) : "r"(a) : "memory"); return v;
}
__device__ __forceinline__ uint32_t lds32u(uint32_t a) {
    uint32_t v; asm volatile("ld.shared.u32 %0, [%1];" : "=r"(v) : "r"(a) : "memory"); return v;
}
__device__ __forceinline__ void sts128(uint32_t a, uint32_t x, uint32_t y, uint32_t z, uint32_t w) {
    asm volatile("st.shared.v4.u32 [%0], {%1,%2,%3,%4};" :: "r"(a), "r"(x), "r"(y), "r"(z), "r"(w) : "memory");
}
__device__ __forceinline__ void sts128f(uint32_t a, float x, float y, float z, float w) {
    asm volatile("st.shared.v4.f32 [%0], {%1,%2,%3,%4};" :: "r"(a), "f"(x), "f"(y), "f"(z), "f"(w) : "memory");
}
__device__ __forceinline__ void sts64f(uint32_t a, float x, float y) {
    asm volatile("st.shared.v2.f32 [%0], {%1,%2};" :: "r"(a), "f"(x), "f"(y) : "memory");
}
__device__ __forceinline__ void sts32(uint32_t a, uint32_t x) {
    asm volatile("st.shared.u32 [%0], %1;" :: "r"(a), "r"(x) : "memory");
}
__device__ __forceinline__ void ldsm_x4_t(uint32_t a, uint32_t& r0, uint32_t& r1, uint32_t& r2, uint32_t& r3) {
    asm volatile("ldmatrix.sync.aligned.m8n8.x4.trans.shared.b16 {%0,%1,%2,%3}, [%4];"
                 : "=r"(r0), "=r"(r1), "=r"(r2), "=r"(r3) : "r"(a) : "memory");
}
__device__ __forceinline__ void mma16816(float (&c)[4], uint32_t a0, uint32_t a1, uint32_t a2, uint32_t a3,
                                         uint32_t b0, uint32_t b1) {
    asm volatile("mma.sync.aligned.m16n8k16.row.col.f32.bf16.bf16.f32 {%0,%1,%2,%3}, {%4,%5,%6,%7}, {%8,%9}, {%0,%1,%2,%3};"
                 : "+f"(c[0]), "+f"(c[1]), "+f"(c[2]), "+f"(c[3])
                 : "r"(a0), "r"(a1), "r"(a2), "r"(a3), "r"(b0), "r"(b1));
}
__device__ __forceinline__ float bf_lo(uint32_t v) { return __uint_as_float(v << 16); }
__device__ __forceinline__ float bf_hi(uint32_t v) { return __uint_as_float(v & 0xffff0000u); }
__device__ __forceinline__ float bf_round(float x) { return __bfloat162float(__float2bfloat16_rn(x)); }
__device__ __forceinline__ uint32_t pack_bf(float lo, float hi) {
    uint32_t r; asm("cvt.rn.bf16x2.f32 %0, %1, %2;" : "=r"(r) : "f"(hi), "f"(lo)); return r;
}
__device__ __forceinline__ uint32_t hadd2_bf(uint32_t a, uint32_t b) {
    uint32_t r; asm("add.rn.bf16x2 %0, %1, %2;" : "=r"(r) : "r"(a), "r"(b)); return r;
}
__device__ __forceinline__ unsigned long long pkt(uint32_t lo, uint32_t hi) { return ((unsigned long long)hi << 32) | lo; }
__device__ __forceinline__ uint32_t tag_of(unsigned long long v) { return (uint32_t)(v >> 32); }
__device__ __forceinline__ uint32_t pay_of(unsigned long long v) { return (uint32_t)v; }
__device__ __forceinline__ void st_pkt(unsigned long long* p, unsigned long long v) {
    asm volatile("st.relaxed.gpu.global.u64 [%0], %1;" :: "l"(p), "l"(v) : "memory");
}
__device__ __forceinline__ void st_pkt2(unsigned long long* p, unsigned long long a, unsigned long long b) {
    asm volatile("st.relaxed.gpu.global.v2.u64 [%0], {%1,%2};" :: "l"(p), "l"(a), "l"(b) : "memory");
}
__device__ __forceinline__ unsigned long long ld_pkt(const unsigned long long* p) {
    unsigned long long v; asm volatile("ld.relaxed.gpu.global.u64 %0, [%1];" : "=l"(v) : "l"(p) : "memory"); return v;
}
__device__ __forceinline__ void ld_pkt2(const unsigned long long* p, unsigned long long& a, unsigned long long& b) {
    asm volatile("ld.relaxed.gpu.global.v2.u64 {%0,%1}, [%2];" : "=l"(a), "=l"(b) : "l"(p) : "memory");
}
__device__ __forceinline__ void st_v4(uint4* p, uint32_t a, uint32_t b, uint32_t c, uint32_t d) {
    asm volatile("st.relaxed.gpu.global.v4.u32 [%0], {%1,%2,%3,%4};" :: "l"(p), "r"(a), "r"(b), "r"(c), "r"(d) : "memory");
}
__device__ __forceinline__ unsigned long long to_fixed(float v) {
    const bool ok = fabsf(v) < 256.0f;
    const long long q = __float2ll_rn((ok ? v : 0.0f) * 0x1p50f);
    return ((unsigned long long)q & ~1023ull) | (ok ? 1u : 33u);
}
__device__ __forceinline__ float gelu_tanh(float x) {
    const float u = 0.7978845608028654f * (x + 0.044715f * x * x * x);
    return 0.5f * x * (1.0f + tanhf(u));
}

__global__ void __launch_bounds__(NTHREADS, 1)
fused_kernel(const __nv_bfloat16* __restrict__ x, const char* __restrict__ kc, const char* __restrict__ vc,
             const __nv_bfloat16* __restrict__ b1, const __nv_bfloat16* __restrict__ b2,
             const __nv_bfloat16* __restrict__ gw, __nv_bfloat16* __restrict__ out,
             const __grid_constant__ CUtensorMap map_wq, const __grid_constant__ CUtensorMap map_w1,
             const __grid_constant__ CUtensorMap map_wo, const __grid_constant__ CUtensorMap map_w2) {
    extern __shared__ unsigned char smem_raw[];
    uint32_t sb = ((uint32_t)__cvta_generic_to_shared(smem_raw) + 1023u) & ~1023u;
    asm volatile("" : "+r"(sb));
    const int tid = threadIdx.x, warp = tid >> 5, lane = tid & 31;
    const int c = blockIdx.x;
    const int hkv = c >> 4, b = (c >> 1) & 7, s = c & 1;
    const int rho = c >> 3, cg = c & 7;
    const int fs = rho * 7 + cg;
    const uint32_t bar_full = sb + OFF_BAR, bar_empty = bar_full + NS * 8, bar_x = bar_empty + NS * 8;

    const size_t kv_off = ((size_t)(b * 8 + hkv) * SK + (SK - WIN) + s * 512) * ROW_BYTES;
    bool leader = false;
    if (warp == 8) {
        leader = elect_one();
        if (leader) {
#pragma unroll
            for (int i = 0; i < POS_FIRST; i++) mbar_init(bar_full + i * 8, 1);
            asm volatile("fence.mbarrier_init.release.cluster;" ::: "memory");
            mbar_expect_tx(bar_full, 224 * 64);
            tma_2d(sb + OFF_RING, &map_wq, 32 * c, 0, bar_full);
            mbar_expect_tx(bar_full + 8, 224 * 64);
            tma_2d(sb + OFF_RING + 224 * 64, &map_wq, 32 * c, 224, bar_full + 8);
#pragma unroll
            for (int i = POS_K; i < POS_FIRST; i++) {
                mbar_expect_tx(bar_full + i * 8, TILE_BYTES);
                bulk_g2s(sb + OFF_RING + i * TILE_BYTES, kc + kv_off + (i - POS_K) * TILE_BYTES, TILE_BYTES, bar_full + i * 8);
            }
        }
    }
    asm volatile("" ::: "memory");

    if (warp == 8) {
        if (leader) {
#pragma unroll
            for (int i = POS_FIRST; i < NS; i++) mbar_init(bar_full + i * 8, 1);
#pragma unroll
            for (int i = 0; i < NS; i++) mbar_init(bar_empty + i * 8, 4);
#pragma unroll
            for (int i = 0; i < 7; i++) mbar_init(bar_x + i * 8, 1);
            mbar_init(bar_x + B_OS, 4);
            asm volatile("fence.mbarrier_init.release.cluster;" ::: "memory");
        }
        __syncwarp();
        bar_arrive(2, NTHREADS);
        if (leader) {
            asm volatile("prefetch.tensormap [%0];" :: "l"(&map_w1) : "memory");
            asm volatile("prefetch.tensormap [%0];" :: "l"(&map_w2) : "memory");
            asm volatile("prefetch.tensormap [%0];" :: "l"(&map_wo) : "memory");
        }
        int slot = POS_FIRST, ph = 1;
        int landed = 0, lslot = 0, lph = 0;
        uint32_t due = gtime32() + PACE_T0;
        auto acquire = [&](int pos) {
            unsigned n = 0;
            while ((int)(gtime32() - due) < 0 && ++n < SPIN_LIMIT) {
                if (landed < pos && landed < POS_W2 && mbar_test(bar_full + lslot * 8, lph)) {
                    landed++;
                    if (++lslot == NS) { lslot = 0; lph ^= 1; }
                }
                if (pos - landed < DEPTH_LO) break;
            }
            due += (pos >= POS_W2 - 1) ? PACE_W : PACE_NS;
            const int depth = (pos >= POS_W2) ? DEPTH_W : DEPTH_HI;
            while (pos - landed >= depth && landed < POS_W2) {
                mbar_wait(bar_full + lslot * 8, lph);
                landed++;
                if (++lslot == NS) { lslot = 0; lph ^= 1; }
            }
            if (pos >= NS) mbar_wait(bar_empty + slot * 8, ph);
        };
        const char* src = kc + kv_off + (POS_FIRST - POS_K) * TILE_BYTES;
#pragma unroll 1
        for (int pos = POS_FIRST; pos < POS_W2; pos++) {
            acquire(pos);
            const uint32_t dst = sb + OFF_RING + slot * TILE_BYTES, bar = bar_full + slot * 8;
            if (pos == POS_GO && leader) mbar_arrive(bar_x + B_GO);
            if (pos == POS_W1) {
                if (leader) {
                    if (cg < 7) {
                        mbar_expect_tx(bar, 448 * 32);
                        tma_2d(dst, &map_w1, 16 * fs, 0, bar);
                        tma_2d(dst + 224 * 32, &map_w1, 16 * fs, 224, bar);
                    } else {
                        mbar_arrive(bar);
                    }
                }
                src = vc + kv_off;
            } else {
                if (leader) {
                    if (pos >= POS_W2 - 2) {
                        const uint32_t bar2 = bar_x + B_VLAST + (pos - (POS_W2 - 2)) * 8;
                        mbar_expect_tx(bar, TILE_BYTES / 2);
                        mbar_expect_tx(bar2, TILE_BYTES / 2);
                        bulk_g2s(dst, src, TILE_BYTES / 2, bar);
                        bulk_g2s(dst + TILE_BYTES / 2, src + TILE_BYTES / 2, TILE_BYTES / 2, bar2);
                    } else {
                        mbar_expect_tx(bar, TILE_BYTES);
                        bulk_g2s(dst, src, TILE_BYTES, bar);
                    }
                }
                src += TILE_BYTES;
            }
            if (++slot == NS) { slot = 0; ph ^= 1; }
        }
        if (cg == 7) return;
        due += PACE_WGAP;
        acquire(POS_W2);
        if (leader) {
            mbar_expect_tx(bar_x + B_W2, 112 * 128);
            tma_2d(sb + OFF_RING + (POS_W2 % NS) * TILE_BYTES, &map_w2, 64 * cg, 112 * rho, bar_x + B_W2);
        }
        if (++slot == NS) { slot = 0; ph ^= 1; }
        const uint32_t wdst = sb + OFF_RING + (POS_WO % NS) * TILE_BYTES;
        acquire(POS_WO);
        if (leader) {
            mbar_expect_tx(bar_x + B_WO0, 4 * 4096);
#pragma unroll
            for (int i = 0; i < 4; i++) tma_2d(wdst + i * 4096, &map_wo, 64 * cg, 256 * rho + 32 * i, bar_x + B_WO0);
        }
        if (++slot == NS) { slot = 0; ph ^= 1; }
        acquire(POS_WO + 1);
        if (leader) {
            mbar_expect_tx(bar_x + B_WO1, 3 * 4096);
            mbar_expect_tx(bar_x + B_WO2, 4096);
#pragma unroll
            for (int i = 4; i < 8; i++)
                tma_2d(wdst + i * 4096, &map_wo, 64 * cg, 256 * rho + 32 * i, bar_x + (i < 7 ? B_WO1 : B_WO2));
        }
        return;
    }

    if (warp > 8) {
        const int mt = warp - 9;
        bar_sync(2, NTHREADS);
        if (cg == 7) return;
        mbar_wait(bar_x + B_GO, 0);
        const uint32_t tag = lds32u(sb + OFF_TG), par = tag & 1;
        const int ocol = 64 * cg + 16 * mt + (lane >> 2), ob = 2 * (lane & 3);
        unsigned long long* acc_p = &g_acc[(cg * 4 + mt) * 128 + lane];
        uint4* pbase = &g_pbuf[(cg * 4 + mt) * 512 + lane];
        __nv_bfloat16* out_p = out + ob * D_MODEL + ocol;
        asm volatile("" : "+l"(acc_p), "+l"(pbase), "+l"(out_p));
        auto bias_of = [&](int e) {
            return lds32f(sb + OFF_ST + (ob + (e & 1)) * 8 + 4) * __bfloat162float(b2[ocol + 8 * (e >> 1)]);
        };
        if (rho == 0) {
#pragma unroll
            for (int e = 0; e < 4; e++)
                asm volatile("red.relaxed.gpu.global.add.u64 [%0], %1;" :: "l"(acc_p + e * 32), "l"(to_fixed(bias_of(e))) : "memory");
        }
        uint32_t hf[7][2];
        {
            const unsigned long long* hsrc = &g_hbuf[(rho * 7 * 32 + lane) * 2];
            unsigned n = 0; bool ok;
            do {
                unsigned long long ha[7], hb[7];
#pragma unroll
                for (int i = 0; i < 7; i++) ld_pkt2(hsrc + i * 64, ha[i], hb[i]);
                ok = true;
#pragma unroll
                for (int i = 0; i < 7; i++) {
                    ok = ok && tag_of(ha[i]) == tag && tag_of(hb[i]) == tag;
                    hf[i][0] = pay_of(ha[i]); hf[i][1] = pay_of(hb[i]);
                }
                if (++n > SPIN_LIMIT) __trap();
            } while (!__all_sync(0xffffffffu, ok));
        }
        const int csw = 2 * mt + ((lane >> 3) & 1);
        float cc[4][4];
#pragma unroll
        for (int i = 0; i < 4; i++) { cc[i][0] = cc[i][1] = cc[i][2] = cc[i][3] = 0.f; }
        uint32_t os_l = sb + OFF_OS + lane * 16;
        asm volatile("" : "+r"(os_l));
        mbar_wait(bar_x + B_W2, 0);
        {
            const uint32_t wb = sb + OFF_RING + (POS_W2 % NS) * TILE_BYTES
                              + ((lane & 7) + ((lane >> 4) << 3)) * 128 + ((csw ^ (lane & 7)) << 4);
#pragma unroll
            for (int i = 0; i < 7; i++) {
                uint32_t a0, a1, a2, a3;
                ldsm_x4_t(wb + i * 2048, a0, a1, a2, a3);
                mma16816(cc[i & 3], a0, a1, a2, a3, hf[i][0], hf[i][1]);
            }
        }
        const int prow = 4 * ((lane & 7) >> 1) + (lane & 1) + ((((lane >> 4) ^ (lane >> 2)) & 1) << 1);
        uint32_t wb = sb + OFF_RING + (POS_WO % NS) * TILE_BYTES + prow * 128 + ((csw ^ (prow & 7)) << 4);
        asm volatile("" : "+r"(wb));
        uint32_t wf[16][4];
        uint4 of[8];
        auto load_w = [&](int lo, int hi) {
#pragma unroll
            for (int i = 0; i < 16; i++)
                if (i >= lo && i < hi) ldsm_x4_t(wb + i * 2048, wf[i][0], wf[i][1], wf[i][2], wf[i][3]);
        };
        auto mm = [&](int lo, int hi) {
#pragma unroll
            for (int i = 0; i < 16; i++)
                if (i >= lo && i < hi)
                    mma16816(cc[i & 3], wf[i][0], wf[i][1], wf[i][2], wf[i][3],
                             (i & 1) ? of[i >> 1].z : of[i >> 1].x, (i & 1) ? of[i >> 1].w : of[i >> 1].y);
        };
        mbar_wait(bar_x + B_WO0, 0);
        load_w(0, 8);
        mbar_wait(bar_x + B_WO1, 0);
        load_w(8, 14);
        const bool have2 = mbar_test(bar_x + B_WO2, 0);
        if (have2) load_w(14, 16);
        mbar_wait(bar_x + B_OS, 0);
#pragma unroll
        for (int i = 0; i < 8; i++) of[i] = lds128(os_l + i * 512);
        mm(0, 14);
        if (!have2) { mbar_wait(bar_x + B_WO2, 0); load_w(14, 16); }
        mm(14, 16);
        float res[4];
        unsigned long long tot[4], add[4];
#pragma unroll
        for (int e = 0; e < 4; e++) {
            res[e] = (cc[0][e] + cc[1][e]) + (cc[2][e] + cc[3][e]);
            add[e] = to_fixed(res[e]);
            asm volatile("atom.relaxed.gpu.global.add.u64 %0, [%1], %2;" : "=l"(tot[e]) : "l"(acc_p + e * 32), "l"(add[e]) : "memory");
        }
        st_v4(pbase + rho * 32, (__float_as_uint(res[0]) & ~1u) | par, (__float_as_uint(res[1]) & ~1u) | par,
                                (__float_as_uint(res[2]) & ~1u) | par, (__float_as_uint(res[3]) & ~1u) | par);
        uint32_t slow = 0;
#pragma unroll
        for (int e = 0; e < 4; e++) {
            tot[e] += add[e];
            const bool last = ((uint32_t)tot[e] & 31) == 17;
            const float val = (float)(long long)tot[e] * 0x1p-50f;
            const bool good = ((uint32_t)tot[e] & 0x3e0) == 0 && fabsf(val) >= 0x1p-24f;
            const __nv_bfloat16 r = __float2bfloat16_rn(val);
            if (last && good)
                asm volatile("st.global.u16 [%0], %1;" :: "l"(out_p + (e & 1) * D_MODEL + 8 * (e >> 1)), "h"(__bfloat16_as_ushort(r)) : "memory");
            if (last) asm volatile("st.relaxed.gpu.global.u64 [%0], %1;" :: "l"(acc_p + e * 32), "l"(0ull) : "memory");
            if (last && !good) slow |= 1u << e;
            if (e == 0 && last && cg == 0 && tid == 288)
                asm volatile("st.relaxed.gpu.global.u32 [%0], %1;" :: "l"(&g_epoch), "r"(tag) : "memory");
        }
        if (slow) {
#pragma unroll 1
            for (int e = 0; e < 4; e++) {
                if (!((slow >> e) & 1)) continue;
                float r = bias_of(e);
#pragma unroll 1
                for (int sr = 0; sr < 16; sr++) {
                    const uint32_t* q = reinterpret_cast<const uint32_t*>(pbase + sr * 32) + e;
                    uint32_t u; unsigned m = 0;
                    do {
                        asm volatile("ld.relaxed.gpu.global.u32 %0, [%1];" : "=r"(u) : "l"(q) : "memory");
                        if (++m > SPIN_LIMIT) __trap();
                    } while ((u & 1) != par);
                    r += __uint_as_float(u & ~1u);
                }
                out_p[(e & 1) * D_MODEL + 8 * (e >> 1)] = __float2bfloat16_rn(r);
            }
        }
        return;
    }

    const int g = lane >> 2, t = lane & 3;
    const uint32_t t_begin = gtime32();
    uint32_t epoch;
    asm volatile("ld.relaxed.gpu.global.u32 %0, [%1];" : "=r"(epoch) : "l"(&g_epoch) : "memory");
    uint32_t b1v = 0;
    if (cg < 7) b1v = *reinterpret_cast<const uint32_t*>(b1 + 16 * fs + 2 * (((tid >> 1) & 3) + 4 * (tid & 1)));

    {
        uint32_t xr[7], gr[7];
#pragma unroll
        for (int i = 0; i < 7; i++) {
            xr[i] = *reinterpret_cast<const uint32_t*>(x + warp * D_MODEL + 2 * (lane + 32 * i));
            gr[i] = *reinterpret_cast<const uint32_t*>(gw + 2 * (lane + 32 * i));
        }
        float sum = 0.f, gz = 0.f;
#pragma unroll
        for (int i = 0; i < 7; i++) {
            sts32(sb + OFF_XS + warp * XS_PITCH + (lane + 32 * i) * 4, xr[i]);
            sum += bf_lo(xr[i]) + bf_hi(xr[i]);
            gz += bf_round(bf_lo(xr[i]) * bf_lo(gr[i])) + bf_round(bf_hi(xr[i]) * bf_hi(gr[i]));
        }
#pragma unroll
        for (int o = 16; o; o >>= 1) { sum += __shfl_xor_sync(0xffffffffu, sum, o); gz += __shfl_xor_sync(0xffffffffu, gz, o); }
        const float mean = sum * (1.0f / D_MODEL);
        float var = 0.f;
#pragma unroll
        for (int i = 0; i < 7; i++) {
            const float d0 = bf_lo(xr[i]) - mean, d1 = bf_hi(xr[i]) - mean;
            var += d0 * d0 + d1 * d1;
        }
#pragma unroll
        for (int o = 16; o; o >>= 1) var += __shfl_xor_sync(0xffffffffu, var, o);
        const float den = bf_round(sqrtf(bf_round(bf_round(var * (1.0f / D_MODEL)) + 1e-5f)));
        const float mb = bf_round(mean);
#pragma unroll
        for (int i = 0; i < 7; i++) {
            sts32(sb + OFF_YS + warp * XS_PITCH + (lane + 32 * i) * 4,
                  pack_bf(__fdividef(bf_round(bf_lo(xr[i]) - mb), den), __fdividef(bf_round(bf_hi(xr[i]) - mb), den)));
        }
        if (lane == 0) {
            const float gt = bf_round(__fdividef(1.0f, 1.0f + __expf(-bf_round(gz))));
            sts64f(sb + OFF_ST + warp * 8, gt, bf_round(1.0f - gt));
        }
    }
    const uint32_t tag = (epoch + 1) ? epoch + 1 : 2;
    if (tid == 0) sts32(sb + OFF_TG, tag);
    bar_sync(2, NTHREADS);

    {
        const int mt = warp & 1, kq = warp >> 1;
        const int row = 112 * kq + (lane & 7) + ((lane >> 4) << 3);
        const uint32_t wa = sb + OFF_RING + row * 64 + (((2 * mt + ((lane >> 3) & 1)) ^ ((row >> 1) & 3)) << 4);
        const uint32_t xa = sb + OFF_XS + g * XS_PITCH + (112 * kq + 2 * t) * 2;
        uint32_t xb[7][2];
#pragma unroll
        for (int ks = 0; ks < 7; ks++) { xb[ks][0] = lds32u(xa + ks * 32); xb[ks][1] = lds32u(xa + ks * 32 + 16); }
        mbar_wait(bar_full + (kq >> 1) * 8, 0);
        float c0[4] = {0.f, 0.f, 0.f, 0.f}, c1[4] = {0.f, 0.f, 0.f, 0.f};
#pragma unroll
        for (int ks = 0; ks < 7; ks++) {
            uint32_t a0, a1, a2, a3;
            ldsm_x4_t(wa + ks * 1024, a0, a1, a2, a3);
            if (ks & 1) mma16816(c1, a0, a1, a2, a3, xb[ks][0], xb[ks][1]);
            else mma16816(c0, a0, a1, a2, a3, xb[ks][0], xb[ks][1]);
        }
        sts128f(sb + OFF_U + warp * 512 + lane * 16, c0[0] + c1[0], c0[1] + c1[1], c0[2] + c1[2], c0[3] + c1[3]);
        bar_sync(1, 256);
        if (tid < 128) {
            const int pb = tid >> 4, p = tid & 15;
            const uint32_t ra = sb + OFF_U + (p >> 3) * 512 + (4 * ((2 * p) & 7) + (pb >> 1)) * 16 + ((p >> 2) & 1) * 8 + (pb & 1) * 4;
            float v0 = 0.f, v1 = 0.f;
#pragma unroll
            for (int w = 0; w < 4; w++) { v0 += lds32f(ra + w * 1024); v1 += lds32f(ra + w * 1024 + 64); }
            st_pkt(&g_qbuf[(hkv * 8 + pb) * 256 + (c & 15) * 16 + p], pkt(pack_bf(v0, v1), tag));
        } else if (tid == 128) {
            mbar_arrive_n(bar_empty, 4);
            mbar_arrive_n(bar_empty + 8, 4);
        }
    }
    {
        const unsigned long long* qsrc = &g_qbuf[(hkv * 8 + b) * 256 + tid];
        unsigned long long v;
        unsigned n = 0;
        while ((int)(gtime32() - t_begin) < QPOLL_T && ++n < SPIN_LIMIT) { }
        n = 0;
        do { v = ld_pkt(qsrc); if (++n > SPIN_LIMIT) __trap(); } while (tag_of(v) != tag);
        sts32(sb + OFF_QS + tid * 4, pay_of(v));
    }
    bar_sync(1, 256);

    int slot = POS_K + (warp >> 2), ph = 0;
    const int r4 = lane >> 3, j8 = lane & 7;
    {
        float qr[2][4][8];
#pragma unroll
        for (int h = 0; h < 2; h++)
#pragma unroll
            for (int i = 0; i < 4; i++) {
                const uint4 u = lds128(sb + OFF_QS + h * 512 + i * 128 + j8 * 16);
                qr[h][i][0] = bf_lo(u.x); qr[h][i][1] = bf_hi(u.x); qr[h][i][2] = bf_lo(u.y); qr[h][i][3] = bf_hi(u.y);
                qr[h][i][4] = bf_lo(u.z); qr[h][i][5] = bf_hi(u.z); qr[h][i][6] = bf_lo(u.w); qr[h][i][7] = bf_hi(u.w);
            }
        const uint32_t koff = (8 * (warp & 3) + r4) * ROW_BYTES + j8 * 16;
        const uint32_t soff = sb + OFF_U + (8 * warp + 4 * (j8 >> 2) + r4) * 8 + ((j8 >> 1) & 1) * 4;
#pragma unroll 1
        for (int it = 0; it < 8; it++) {
            mbar_wait(bar_full + slot * 8, ph);
            const uint32_t base = sb + OFF_RING + slot * TILE_BYTES + koff;
            uint4 la[4], lb[4];
#pragma unroll
            for (int i = 0; i < 4; i++) { la[i] = lds128(base + i * 128); lb[i] = lds128(base + 4 * ROW_BYTES + i * 128); }
            float a0 = 0.f, a1 = 0.f, b0 = 0.f, b1_ = 0.f;
#pragma unroll
            for (int i = 0; i < 4; i++) {
                const uint32_t wa[4] = {la[i].x, la[i].y, la[i].z, la[i].w}, wb[4] = {lb[i].x, lb[i].y, lb[i].z, lb[i].w};
#pragma unroll
                for (int e = 0; e < 4; e++) {
                    const float al = bf_lo(wa[e]), ah = bf_hi(wa[e]), bl = bf_lo(wb[e]), bh = bf_hi(wb[e]);
                    a0 = fmaf(al, qr[0][i][2 * e], a0); a1 = fmaf(al, qr[1][i][2 * e], a1);
                    b0 = fmaf(bl, qr[0][i][2 * e], b0); b1_ = fmaf(bl, qr[1][i][2 * e], b1_);
                    a0 = fmaf(ah, qr[0][i][2 * e + 1], a0); a1 = fmaf(ah, qr[1][i][2 * e + 1], a1);
                    b0 = fmaf(bh, qr[0][i][2 * e + 1], b0); b1_ = fmaf(bh, qr[1][i][2 * e + 1], b1_);
                }
            }
            __syncwarp();
            if (lane == 0) mbar_arrive(bar_empty + slot * 8);
            const bool up = j8 & 4;
            const float k0 = (up ? b0 : a0) + __shfl_xor_sync(0xffffffffu, up ? a0 : b0, 4);
            const float k1 = (up ? b1_ : a1) + __shfl_xor_sync(0xffffffffu, up ? a1 : b1_, 4);
            const bool up2 = j8 & 2;
            float r = (up2 ? k1 : k0) + __shfl_xor_sync(0xffffffffu, up2 ? k0 : k1, 2);
            r += __shfl_xor_sync(0xffffffffu, r, 1);
            if ((lane & 1) == 0) sts32(soff + it * 512, __float_as_uint(r));
            slot += 2; if (slot >= NS) { slot -= NS; ph ^= 1; }
        }
        slot += 1; if (slot >= NS) { slot -= NS; ph ^= 1; }
    }
    if (warp < 4 && cg < 7) {
        const int row = 112 * warp + (lane & 7) + ((lane >> 4) << 3);
        const uint32_t wa = sb + OFF_RING + (POS_W1 % NS) * TILE_BYTES + row * 32 + ((((lane >> 3) & 1) ^ ((row >> 2) & 1)) << 4);
        const uint32_t ya = sb + OFF_YS + g * XS_PITCH + (112 * warp + 2 * t) * 2;
        mbar_wait(bar_full + (POS_W1 % NS) * 8, (POS_W1 / NS) & 1);
        float c0[4] = {0.f, 0.f, 0.f, 0.f};
#pragma unroll
        for (int ks = 0; ks < 7; ks++) {
            uint32_t a0, a1, a2, a3;
            ldsm_x4_t(wa + ks * 512, a0, a1, a2, a3);
            mma16816(c0, a0, a1, a2, a3, lds32u(ya + ks * 32), lds32u(ya + ks * 32 + 16));
        }
        sts128f(sb + OFF_HR + warp * 512 + lane * 16, c0[0], c0[1], c0[2], c0[3]);
    }
    bar_sync(1, 256);
    if (tid == 255) {
        mbar_wait(bar_full + (POS_W1 % NS) * 8, (POS_W1 / NS) & 1);
        mbar_arrive_n(bar_empty + (POS_W1 % NS) * 8, 4);
    }
    float own_m, own_l;
    {
        const uint4 p0 = lds128(sb + OFF_U + tid * 16);
        const float s00 = bf_round(__uint_as_float(p0.x)) * 0.0625f;
        const float s01 = bf_round(__uint_as_float(p0.y)) * 0.0625f;
        const float s10 = bf_round(__uint_as_float(p0.z)) * 0.0625f;
        const float s11 = bf_round(__uint_as_float(p0.w)) * 0.0625f;
        float m0 = fmaxf(s00, s10), m1 = fmaxf(s01, s11);
        __syncwarp();
#pragma unroll
        for (int o = 16; o; o >>= 1) {
            m0 = fmaxf(m0, __shfl_xor_sync(0xffffffffu, m0, o));
            m1 = fmaxf(m1, __shfl_xor_sync(0xffffffffu, m1, o));
        }
        if (lane == 0) sts64f(sb + OFF_WM + warp * 8, m0, m1);
        if (tid < 64 && cg < 7) {
            const int L = tid >> 1, hf = tid & 1, pb = L >> 2;
            const uint32_t ra = sb + OFF_HR + (4 * (2 * (L & 3)) + (pb >> 1)) * 16 + hf * 8 + (pb & 1) * 4;
            float v0 = 0.f, v1 = 0.f;
#pragma unroll
            for (int w = 0; w < 4; w++) { v0 += lds32f(ra + w * 512); v1 += lds32f(ra + w * 512 + 64); }
            const float omg = lds32f(sb + OFF_ST + pb * 8 + 4);
            v0 = bf_round(gelu_tanh(bf_round(bf_round(v0) + bf_lo(b1v)))) * omg;
            v1 = bf_round(gelu_tanh(bf_round(bf_round(v1) + bf_hi(b1v)))) * omg;
            st_pkt(&g_hbuf[(fs * 32 + L) * 2 + hf], pkt(pack_bf(v0, v1), tag));
        }
        bar_sync(1, 256);
#pragma unroll
        for (int w = 0; w < 4; w++) {
            const uint4 v = lds128(sb + OFF_WM + w * 16);
            m0 = fmaxf(m0, fmaxf(__uint_as_float(v.x), __uint_as_float(v.z)));
            m1 = fmaxf(m1, fmaxf(__uint_as_float(v.y), __uint_as_float(v.w)));
        }
        const float e00 = __expf(s00 - m0), e10 = __expf(s10 - m0), e01 = __expf(s01 - m1), e11 = __expf(s11 - m1);
        {
            const uint32_t pa = sb + OFF_PS + (tid >> 4) * 256 + (tid & 1) * 128 + ((tid >> 1) & 7) * 8;
            sts64f(pa, e00, e01);
            sts64f(pa + 64, e10, e11);
        }
        float l0 = e00 + e10, l1 = e01 + e11;
#pragma unroll
        for (int o = 16; o; o >>= 1) { l0 += __shfl_xor_sync(0xffffffffu, l0, o); l1 += __shfl_xor_sync(0xffffffffu, l1, o); }
        if (lane == 0) sts64f(sb + OFF_WS + warp * 8, l0, l1);
        bar_sync(1, 256);
        const int hh = lane >> 4;
        float l = 0.f;
#pragma unroll
        for (int w = 0; w < 8; w++) l += lds32f(sb + OFF_WS + w * 8 + hh * 4);
        own_m = hh ? m1 : m0; own_l = l;
        if ((tid & ~16) == 0)
            st_pkt2(&g_mlbuf[c * 4 + hh * 2], pkt(__float_as_uint(own_m), tag), pkt(__float_as_uint(l), tag));
    }
    float acc[2][8];
#pragma unroll
    for (int i = 0; i < 8; i++) { acc[0][i] = acc[1][i] = 0.f; }
    const int dq = warp & 3;
    const unsigned long long* msrc = &g_mlbuf[(c ^ 1) * 4 + (lane >> 4) * 2];
    unsigned long long pm = 0, pl = 0;
    float scale = 0.f;
    unsigned long long* const odst =
        &g_obuf[((((2 * hkv + (r4 >> 1)) * 2 + s) * 8 + 2 * dq + (j8 >> 2)) * 32 + b * 4 + 2 * (j8 & 1) + (r4 & 1)) * 2 + ((j8 >> 1) & 1)];
    {
        const uint32_t poff = sb + OFF_PS + (warp >> 2) * 256 + r4 * 64;
        const uint32_t voff = r4 * ROW_BYTES + dq * 128 + j8 * 16;
        auto rows = [&](const uint4 (&r)[4], const uint4& pa, const uint4& pb) {
#pragma unroll
            for (int j = 0; j < 4; j++) {
                const uint4& pp = (j & 2) ? pb : pa;
                const float p0 = __uint_as_float((j & 1) ? pp.z : pp.x), p1 = __uint_as_float((j & 1) ? pp.w : pp.y);
                const uint32_t wv[4] = {r[j].x, r[j].y, r[j].z, r[j].w};
#pragma unroll
                for (int e = 0; e < 4; e++) {
                    const float lo = bf_lo(wv[e]), hi = bf_hi(wv[e]);
                    acc[0][2 * e] = fmaf(lo, p0, acc[0][2 * e]); acc[1][2 * e] = fmaf(lo, p1, acc[1][2 * e]);
                    acc[0][2 * e + 1] = fmaf(hi, p0, acc[0][2 * e + 1]); acc[1][2 * e + 1] = fmaf(hi, p1, acc[1][2 * e + 1]);
                }
            }
        };
#pragma unroll 1
        for (int i = 0; i < 8; i++) {
            uint4 pf[4];
#pragma unroll
            for (int j = 0; j < 4; j++) pf[j] = lds128(poff + i * 512 + j * 16);
            if (i == PRE_IT && warp >= 4) {
                ld_pkt2(msrc, pm, pl);
                st_pkt(odst, (unsigned long long)((tag & 1) ^ 1));
            }
            if (i == PRE_IT + 3 && warp >= 4) {
                unsigned n = 0;
                while (tag_of(pm) != tag || tag_of(pl) != tag) { ld_pkt2(msrc, pm, pl); if (++n > SPIN_LIMIT) __trap(); }
                const float m_o = __uint_as_float(pay_of(pm)), l_o = __uint_as_float(pay_of(pl));
                const float m = fmaxf(own_m, m_o);
                const float e_s = __expf(own_m - m), e_o = __expf(m_o - m);
                scale = __fdividef(lds32f(sb + OFF_ST + b * 8) * e_s, e_s * own_l + e_o * l_o);
                __syncwarp();
            }
            mbar_wait(bar_full + slot * 8, ph);
            const uint32_t base = sb + OFF_RING + slot * TILE_BYTES + voff;
            uint4 ra[4], rb[4];
#pragma unroll
            for (int j = 0; j < 4; j++) ra[j] = lds128(base + j * 4 * ROW_BYTES);
            if (i == 7) {
                rows(ra, pf[0], pf[1]);
                mbar_wait(bar_x + B_VLAST + (warp >> 2) * 8, 0);
#pragma unroll
                for (int j = 0; j < 4; j++) rb[j] = lds128(base + (j + 4) * 4 * ROW_BYTES);
                rows(rb, pf[2], pf[3]);
                break;
            }
#pragma unroll
            for (int j = 0; j < 4; j++) rb[j] = lds128(base + (j + 4) * 4 * ROW_BYTES);
            rows(ra, pf[0], pf[1]);
            rows(rb, pf[2], pf[3]);
            __syncwarp();
            if (lane == 0) mbar_arrive(bar_empty + slot * 8);
            slot += 2; if (slot >= NS) { slot -= NS; ph ^= 1; }
        }
    }
    const bool up = lane & 16, up2 = lane & 8;
    float u[8], v[4];
#pragma unroll
    for (int e = 0; e < 8; e++) u[e] = (up ? acc[1][e] : acc[0][e]) + __shfl_xor_sync(0xffffffffu, up ? acc[0][e] : acc[1][e], 16);
#pragma unroll
    for (int e = 0; e < 4; e++) v[e] = (up2 ? u[e + 4] : u[e]) + __shfl_xor_sync(0xffffffffu, up2 ? u[e] : u[e + 4], 8);
    const uint32_t xa = sb + OFF_U + dq * 512 + lane * 16;
    if (warp >= 4) {
        bar_sync(5 + dq, 64);
        const uint4 o = lds128(xa);
        const float x0 = (v[0] + __uint_as_float(o.x)) * scale, x1 = (v[1] + __uint_as_float(o.y)) * scale;
        const float x2 = (v[2] + __uint_as_float(o.z)) * scale, x3 = (v[3] + __uint_as_float(o.w)) * scale;
        const bool sw = j8 & 1;
        const float v0 = sw ? x2 : x0, v1 = sw ? x3 : x1, v2 = sw ? x0 : x2, v3 = sw ? x1 : x3;
        const uint32_t w0 = (pack_bf(v0, v1) & 0xffff0000u) | (((__float_as_uint(v0) + 0x10000u) >> 16) & 0xfffeu) | (tag & 1);
        st_pkt(odst, pkt(w0, pack_bf(v2, v3)));
        return;
    }
    sts128f(xa, v[0], v[1], v[2], v[3]);
    bar_arrive(5 + dq, 64);
    if (cg == 7) return;
    {
        const uint32_t par = tag & 1;
        const unsigned long long* osrc = &g_obuf[((rho * 2 * 8 + 2 * dq) * 32 + lane) * 2];
        unsigned long long pa[4], pb[4];
        mbar_wait(bar_x + B_WO0, 0);
        ld_pkt2(osrc, pa[0], pb[0]);
        ld_pkt2(osrc + 512, pa[1], pb[1]);
        ld_pkt2(osrc + 64, pa[2], pb[2]);
        ld_pkt2(osrc + 512 + 64, pa[3], pb[3]);
        unsigned n = 0;
        while (true) {
            bool okk[4];
#pragma unroll
            for (int i = 0; i < 4; i++) okk[i] = ((((uint32_t)pa[i] ^ par) | ((uint32_t)pb[i] ^ par)) & 1) == 0;
            if (__all_sync(0xffffffffu, okk[0] && okk[1] && okk[2] && okk[3])) break;
            if (!okk[0]) ld_pkt2(osrc, pa[0], pb[0]);
            if (!okk[1]) ld_pkt2(osrc + 512, pa[1], pb[1]);
            if (!okk[2]) ld_pkt2(osrc + 64, pa[2], pb[2]);
            if (!okk[3]) ld_pkt2(osrc + 512 + 64, pa[3], pb[3]);
            if (++n > SPIN_LIMIT) __trap();
        }
#pragma unroll
        for (int i = 0; i < 2; i++) {
            sts128(sb + OFF_OS + lane * 16 + dq * 1024 + i * 512,
                   hadd2_bf((uint32_t)pa[2 * i] & ~1u, (uint32_t)pa[2 * i + 1] & ~1u),
                   hadd2_bf((uint32_t)(pa[2 * i] >> 32), (uint32_t)(pa[2 * i + 1] >> 32)),
                   hadd2_bf((uint32_t)pb[2 * i] & ~1u, (uint32_t)pb[2 * i + 1] & ~1u),
                   hadd2_bf((uint32_t)(pb[2 * i] >> 32), (uint32_t)(pb[2 * i + 1] >> 32)));
        }
        __syncwarp();
        if (lane == 0) mbar_arrive(bar_x + B_OS);
    }
}

typedef CUresult (*EncodeFn)(CUtensorMap*, CUtensorMapDataType, cuuint32_t, void*, const cuuint64_t*, const cuuint64_t*,
                             const cuuint32_t*, const cuuint32_t*, CUtensorMapInterleave, CUtensorMapSwizzle,
                             CUtensorMapL2promotion, CUtensorMapFloatOOBfill);

bool make_map(EncodeFn fn, CUtensorMap* m, const void* ptr, int cols, int rows, int box_cols, int box_rows,
              CUtensorMapSwizzle swz) {
    cuuint64_t dims[2] = {(cuuint64_t)cols, (cuuint64_t)rows};
    cuuint64_t strides[1] = {(cuuint64_t)cols * 2};
    cuuint32_t box[2] = {(cuuint32_t)box_cols, (cuuint32_t)box_rows};
    cuuint32_t es[2] = {1, 1};
    return fn(m, CU_TENSOR_MAP_DATA_TYPE_BFLOAT16, 2, const_cast<void*>(ptr), dims, strides, box, es,
              CU_TENSOR_MAP_INTERLEAVE_NONE, swz, CU_TENSOR_MAP_L2_PROMOTION_L2_128B,
              CU_TENSOR_MAP_FLOAT_OOB_FILL_NONE) == CUDA_SUCCESS;
}

}

extern "C" void kernel_launch(void* const* d_in, const int* in_sizes, int n_in, void* d_out, int out_size) {
    (void)in_sizes; (void)n_in; (void)out_size;
    static EncodeFn enc = nullptr;
    if (!enc) {
        void* fn = nullptr;
        cudaDriverEntryPointQueryResult qr;
        cudaGetDriverEntryPoint("cuTensorMapEncodeTiled", &fn, cudaEnableDefault, &qr);
        enc = (EncodeFn)fn;
        if (!enc) return;
        cudaFuncSetAttribute(fused_kernel, cudaFuncAttributeMaxDynamicSharedMemorySize, SMEM_BYTES);
    }
    CUtensorMap map_wq, map_w1, map_wo, map_w2;
    bool ok = make_map(enc, &map_wq, d_in[3], N_QCOL, D_MODEL, 32, 224, CU_TENSOR_MAP_SWIZZLE_64B);
    ok = ok && make_map(enc, &map_w1, d_in[6], FF, D_MODEL, 16, 224, CU_TENSOR_MAP_SWIZZLE_32B);
    ok = ok && make_map(enc, &map_wo, d_in[4], D_MODEL, N_QCOL, 64, 32, CU_TENSOR_MAP_SWIZZLE_128B);
    ok = ok && make_map(enc, &map_w2, d_in[8], D_MODEL, FF, 64, 112, CU_TENSOR_MAP_SWIZZLE_128B);
    if (!ok) return;

    cudaLaunchConfig_t cfg = {};
    cfg.gridDim = dim3(NCTA);
    cfg.blockDim = dim3(NTHREADS);
    cfg.dynamicSmemBytes = SMEM_BYTES;
    cfg.stream = cudaStreamPerThread;
    cudaLaunchAttribute at[1];
    at[0].id = cudaLaunchAttributeCooperative;
    at[0].val.cooperative = 1;
    cfg.attrs = at;
    cfg.numAttrs = 1;
    cudaLaunchKernelEx(&cfg, fused_kernel,
                       (const __nv_bfloat16*)d_in[0], (const char*)d_in[1], (const char*)d_in[2],
                       (const __nv_bfloat16*)d_in[7], (const __nv_bfloat16*)d_in[9],
                       (const __nv_bfloat16*)d_in[10], (__nv_bfloat16*)d_out, map_wq, map_w1, map_wo, map_w2);
}
```

```cpp
#include <cuda_runtime.h>
#include <cuda_bf16.h>
#include <cuda.h>
#include <stdint.h>

namespace {

constexpr int D_MODEL = 448;
constexpr int N_QCOL = 4096;
constexpr int SK = 4096;
constexpr int WIN = 1024;
constexpr int FF = 1792;
constexpr int NCTA = 128;
constexpr int NTHREADS = 416;

constexpr int ROW_BYTES = 512;
constexpr int TILE_ROWS = 32;
constexpr int TILE_BYTES = TILE_ROWS * ROW_BYTES;
constexpr int NS = 12;
constexpr int NT = 512 / TILE_ROWS;
constexpr int POS_K = 2, POS_W1 = POS_K + NT, POS_V = POS_W1 + 1, POS_W2 = POS_V + NT, POS_WO = POS_W2 + 1;
static_assert(POS_WO % NS + 2 <= NS, "wo tile must not wrap");
constexpr int POS_GO = POS_V + 6;

constexpr int POS_FIRST = 3;
constexpr int PACE_T0 = 650;
constexpr int PACE_NS = 648;
constexpr int PACE_WGAP = 800;
constexpr int DEPTH_LO = 2;
constexpr int DEPTH_HI = 10;
constexpr int DEPTH_W = 3;
constexpr int QPOLL_T = 4000;
constexpr int PRE_IT = 3;

constexpr int XS_PITCH = 912;

constexpr int OFF_RING = 0;
constexpr int OFF_U = NS * TILE_BYTES;
constexpr int OFF_XS = OFF_U + 8192;
constexpr int OFF_YS = OFF_U + 16384;
constexpr int OFF_OS = OFF_YS;
constexpr int OFF_PS = OFF_YS + 8192;
constexpr int OFF_QS = OFF_PS + 4096;
constexpr int OFF_HR = OFF_QS + 1024;
constexpr int OFF_ST = OFF_HR + 2048;
constexpr int OFF_WM = OFF_ST + 64;
constexpr int OFF_WS = OFF_WM + 64;
constexpr int OFF_TG = OFF_WS + 64;
constexpr int OFF_BAR = OFF_TG + 16;
constexpr int B_W2 = 0, B_WO0 = 8, B_WO1 = 16, B_WO2 = 24, B_GO = 32, B_VLAST = 40  , B_OS = 56;
constexpr int NBAR = 2 * NS + 8;
constexpr int SMEM_BYTES = OFF_BAR + NBAR * 8 + 1024;

constexpr unsigned SPIN_LIMIT = 1u << 22;

__device__ unsigned g_epoch;
__device__ __align__(128) unsigned long long g_qbuf[8 * 8 * 256];
__device__ __align__(128) unsigned long long g_hbuf[16 * 7 * 32 * 2];
__device__ __align__(128) unsigned long long g_mlbuf[NCTA * 4];
__device__ __align__(128) unsigned long long g_obuf[16 * 2 * 8 * 32 * 2];
__device__ __align__(128) uint4 g_pbuf[7 * 4 * 16 * 32];
__device__ __align__(128) unsigned long long g_acc[7 * 4 * 4 * 32];

__device__ __forceinline__ uint32_t gtime32() { uint32_t t; asm volatile("mov.u32 %0, %globaltimer_lo;" : "=r"(t)); return t; }
__device__ __forceinline__ void mbar_init(uint32_t bar, int cnt) {
    asm volatile("mbarrier.init.shared::cta.b64 [%0], %1;" :: "r"(bar), "r"(cnt) : "memory");
}
__device__ __forceinline__ void mbar_expect_tx(uint32_t bar, uint32_t bytes) {
    asm volatile("mbarrier.arrive.expect_tx.shared::cta.b64 _, [%0], %1;" :: "r"(bar), "r"(bytes) : "memory");
}
__device__ __forceinline__ void mbar_arrive(uint32_t bar) {
    asm volatile("mbarrier.arrive.shared::cta.b64 _, [%0];" :: "r"(bar) : "memory");
}
__device__ __forceinline__ void mbar_arrive_n(uint32_t bar, uint32_t n) {
    asm volatile("mbarrier.arrive.shared::cta.b64 _, [%0], %1;" :: "r"(bar), "r"(n) : "memory");
}
__device__ __forceinline__ bool mbar_try(uint32_t bar, uint32_t parity) {
    uint32_t ok;
    asm volatile("{\n.reg .pred p;\nmbarrier.try_wait.parity.shared::cta.b64 p, [%1], %2;\nselp.u32 %0, 1, 0, p;\n}"
                 : "=r"(ok) : "r"(bar), "r"(parity) : "memory");
    return ok != 0;
}
__device__ __forceinline__ bool mbar_test(uint32_t bar, uint32_t parity) {
    uint32_t ok;
    asm volatile("{\n.reg .pred p;\nmbarrier.test_wait.parity.shared::cta.b64 p, [%1], %2;\nselp.u32 %0, 1, 0, p;\n}"
                 : "=r"(ok) : "r"(bar), "r"(parity) : "memory");
    return ok != 0;
}
__device__ __forceinline__ void mbar_wait(uint32_t bar, uint32_t parity) {
    unsigned n = 0;
    while (!mbar_try(bar, parity)) { if (++n > SPIN_LIMIT) __trap(); }
}
constexpr unsigned long long POLICY_EVICT_FIRST = 0x12F0000000000000ull;
__device__ __forceinline__ void bulk_g2s(uint32_t dst, const void* src, uint32_t bytes, uint32_t bar) {
    asm volatile("cp.async.bulk.shared::cluster.global.mbarrier::complete_tx::bytes.L2::cache_hint [%0], [%1], %2, [%3], %4;"
                 :: "r"(dst), "l"(src), "r"(bytes), "r"(bar), "l"(POLICY_EVICT_FIRST) : "memory");
}
__device__ __forceinline__ void tma_2d(uint32_t dst, const CUtensorMap* map, int c0, int c1, uint32_t bar) {
    asm volatile("cp.async.bulk.tensor.2d.shared::cluster.global.mbarrier::complete_tx::bytes [%0], [%1, {%3, %4}], [%2];"
                 :: "r"(dst), "l"(map), "r"(bar), "r"(c0), "r"(c1) : "memory");
}
__device__ __forceinline__ void bar_sync(int id, int n) { asm volatile("bar.sync %0, %1;" :: "r"(id), "r"(n) : "memory"); }
__device__ __forceinline__ void bar_arrive(int id, int n) { asm volatile("bar.arrive %0, %1;" :: "r"(id), "r"(n) : "memory"); }
__device__ __forceinline__ bool elect_one() {
    uint32_t p;
    asm volatile("{\n.reg .pred p;\nelect.sync _|p, 0xffffffff;\nselp.u32 %0, 1, 0, p;\n}" : "=r"(p));
    return p != 0;
}
__device__ __forceinline__ uint4 lds128(uint32_t a) {
    uint4 v; asm volatile("ld.shared.v4.u32 {%0,%1,%2,%3}, [%4];" : "=r"(v.x), "=r"(v.y), "=r"(v.z), "=r"(v.w) : "r"(a) : "memory"); return v;
}
__device__ __forceinline__ float lds32f(uint32_t a) {
    float v; asm volatile("ld.shared.f32 %0, [%1];" : "=f"(v) : "r"(a) : "memory"); return v;
}
__device__ __forceinline__ uint32_t lds32u(uint32_t a) {
    uint32_t v; asm volatile("ld.shared.u32 %0, [%1];" : "=r"(v) : "r"(a) : "memory"); return v;
}
__device__ __forceinline__ void sts128(uint32_t a, uint32_t x, uint32_t y, uint32_t z, uint32_t w) {
    asm volatile("st.shared.v4.u32 [%0], {%1,%2,%3,%4};" :: "r"(a), "r"(x), "r"(y), "r"(z), "r"(w) : "memory");
}
__device__ __forceinline__ void sts128f(uint32_t a, float x, float y, float z, float w) {
    asm volatile("st.shared.v4.f32 [%0], {%1,%2,%3,%4};" :: "r"(a), "f"(x), "f"(y), "f"(z), "f"(w) : "memory");
}
__device__ __forceinline__ void sts64f(uint32_t a, float x, float y) {
    asm volatile("st.shared.v2.f32 [%0], {%1,%2};" :: "r"(a), "f"(x), "f"(y) : "memory");
}
__device__ __forceinline__ void sts32(uint32_t a, uint32_t x) {
    asm volatile("st.shared.u32 [%0], %1;" :: "r"(a), "r"(x) : "memory");
}
__device__ __forceinline__ void ldsm_x4_t(uint32_t a, uint32_t& r0, uint32_t& r1, uint32_t& r2, uint32_t& r3) {
    asm volatile("ldmatrix.sync.aligned.m8n8.x4.trans.shared.b16 {%0,%1,%2,%3}, [%4];"
                 : "=r"(r0), "=r"(r1), "=r"(r2), "=r"(r3) : "r"(a) : "memory");
}
__device__ __forceinline__ void mma16816(float (&c)[4], uint32_t a0, uint32_t a1, uint32_t a2, uint32_t a3,
                                         uint32_t b0, uint32_t b1) {
    asm volatile("mma.sync.aligned.m16n8k16.row.col.f32.bf16.bf16.f32 {%0,%1,%2,%3}, {%4,%5,%6,%7}, {%8,%9}, {%0,%1,%2,%3};"
                 : "+f"(c[0]), "+f"(c[1]), "+f"(c[2]), "+f"(c[3])
                 : "r"(a0), "r"(a1), "r"(a2), "r"(a3), "r"(b0), "r"(b1));
}
__device__ __forceinline__ float bf_lo(uint32_t v) { return __uint_as_float(v << 16); }
__device__ __forceinline__ float bf_hi(uint32_t v) { return __uint_as_float(v & 0xffff0000u); }
__device__ __forceinline__ float bf_round(float x) { return __bfloat162float(__float2bfloat16_rn(x)); }
__device__ __forceinline__ uint32_t pack_bf(float lo, float hi) {
    uint32_t r; asm("cvt.rn.bf16x2.f32 %0, %1, %2;" : "=r"(r) : "f"(hi), "f"(lo)); return r;
}
__device__ __forceinline__ uint32_t hadd2_bf(uint32_t a, uint32_t b) {
    uint32_t r; asm("add.rn.bf16x2 %0, %1, %2;" : "=r"(r) : "r"(a), "r"(b)); return r;
}
__device__ __forceinline__ unsigned long long pkt(uint32_t lo, uint32_t hi) { return ((unsigned long long)hi << 32) | lo; }
__device__ __forceinline__ uint32_t tag_of(unsigned long long v) { return (uint32_t)(v >> 32); }
__device__ __forceinline__ uint32_t pay_of(unsigned long long v) { return (uint32_t)v; }
__device__ __forceinline__ void st_pkt(unsigned long long* p, unsigned long long v) {
    asm volatile("st.relaxed.gpu.global.u64 [%0], %1;" :: "l"(p), "l"(v) : "memory");
}
__device__ __forceinline__ void st_pkt2(unsigned long long* p, unsigned long long a, unsigned long long b) {
    asm volatile("st.relaxed.gpu.global.v2.u64 [%0], {%1,%2};" :: "l"(p), "l"(a), "l"(b) : "memory");
}
__device__ __forceinline__ unsigned long long ld_pkt(const unsigned long long* p) {
    unsigned long long v; asm volatile("ld.relaxed.gpu.global.u64 %0, [%1];" : "=l"(v) : "l"(p) : "memory"); return v;
}
__device__ __forceinline__ void ld_pkt2(const unsigned long long* p, unsigned long long& a, unsigned long long& b) {
    asm volatile("ld.relaxed.gpu.global.v2.u64 {%0,%1}, [%2];" : "=l"(a), "=l"(b) : "l"(p) : "memory");
}
__device__ __forceinline__ void st_v4(uint4* p, uint32_t a, uint32_t b, uint32_t c, uint32_t d) {
    asm volatile("st.relaxed.gpu.global.v4.u32 [%0], {%1,%2,%3,%4};" :: "l"(p), "r"(a), "r"(b), "r"(c), "r"(d) : "memory");
}
__device__ __forceinline__ unsigned long long to_fixed(float v) {
    const bool ok = fabsf(v) < 256.0f;
    const long long q = __float2ll_rn((ok ? v : 0.0f) * 0x1p50f);
    return ((unsigned long long)q & ~1023ull) | (ok ? 1u : 33u);
}
__device__ __forceinline__ float gelu_tanh(float x) {
    const float u = 0.7978845608028654f * (x + 0.044715f * x * x * x);
    return 0.5f * x * (1.0f + tanhf(u));
}

__global__ void __launch_bounds__(NTHREADS, 1)
fused_kernel(const __nv_bfloat16* __restrict__ x, const char* __restrict__ kc, const char* __restrict__ vc,
             const __nv_bfloat16* __restrict__ b1, const __nv_bfloat16* __restrict__ b2,
             const __nv_bfloat16* __restrict__ gw, __nv_bfloat16* __restrict__ out, const int pace_ns,
             const __grid_constant__ CUtensorMap map_wq, const __grid_constant__ CUtensorMap map_w1,
             const __grid_constant__ CUtensorMap map_wo, const __grid_constant__ CUtensorMap map_w2) {
    extern __shared__ unsigned char smem_raw[];
    uint32_t sb = ((uint32_t)__cvta_generic_to_shared(smem_raw) + 1023u) & ~1023u;
    asm volatile("" : "+r"(sb));
    const int tid = threadIdx.x, warp = tid >> 5, lane = tid & 31;
    const int c = blockIdx.x;
    const int hkv = c >> 4, b = (c >> 1) & 7, s = c & 1;
    const int rho = c >> 3, cg = c & 7;
    const int fs = rho * 7 + cg;
    const uint32_t bar_full = sb + OFF_BAR, bar_empty = bar_full + NS * 8, bar_x = bar_empty + NS * 8;

    const size_t kv_off = ((size_t)(b * 8 + hkv) * SK + (SK - WIN) + s * 512) * ROW_BYTES;
    bool leader = false;
    if (warp == 8) {
        leader = elect_one();
        if (leader) {
#pragma unroll
            for (int i = 0; i < POS_FIRST; i++) mbar_init(bar_full + i * 8, 1);
            asm volatile("fence.mbarrier_init.release.cluster;" ::: "memory");
            mbar_expect_tx(bar_full, 224 * 64);
            tma_2d(sb + OFF_RING, &map_wq, 32 * c, 0, bar_full);
            mbar_expect_tx(bar_full + 8, 224 * 64);
            tma_2d(sb + OFF_RING + 224 * 64, &map_wq, 32 * c, 224, bar_full + 8);
#pragma unroll
            for (int i = POS_K; i < POS_FIRST; i++) {
                mbar_expect_tx(bar_full + i * 8, TILE_BYTES);
                bulk_g2s(sb + OFF_RING + i * TILE_BYTES, kc + kv_off + (i - POS_K) * TILE_BYTES, TILE_BYTES, bar_full + i * 8);
            }
        }
    }
    asm volatile("" ::: "memory");

    if (warp == 8) {
        if (leader) {
#pragma unroll
            for (int i = POS_FIRST; i < NS; i++) mbar_init(bar_full + i * 8, 1);
#pragma unroll
            for (int i = 0; i < NS; i++) mbar_init(bar_empty + i * 8, 4);
#pragma unroll
            for (int i = 0; i < 7; i++) mbar_init(bar_x + i * 8, 1);
            mbar_init(bar_x + B_OS, 4);
            asm volatile("fence.mbarrier_init.release.cluster;" ::: "memory");
        }
        __syncwarp();
        bar_arrive(2, NTHREADS);
        if (leader) {
            asm volatile("prefetch.tensormap [%0];" :: "l"(&map_w1) : "memory");
            asm volatile("prefetch.tensormap [%0];" :: "l"(&map_w2) : "memory");
            asm volatile("prefetch.tensormap [%0];" :: "l"(&map_wo) : "memory");
        }
        int slot = POS_FIRST, ph = 1;
        int landed = 0, lslot = 0, lph = 0;
        uint32_t due = gtime32() + PACE_T0;
        auto acquire = [&](int pos) {
            unsigned n = 0;
            while ((int)(gtime32() - due) < 0 && ++n < SPIN_LIMIT) {
                if (landed < pos && landed < POS_W2 && mbar_test(bar_full + lslot * 8, lph)) {
                    landed++;
                    if (++lslot == NS) { lslot = 0; lph ^= 1; }
                }
                if (pos - landed < DEPTH_LO) break;
            }
            due += (pos >= POS_W2 - 1) ? (pace_ns * 11) >> 4 : pace_ns;
            const int depth = (pos >= POS_W2) ? DEPTH_W : DEPTH_HI;
            while (pos - landed >= depth && landed < POS_W2) {
                mbar_wait(bar_full + lslot * 8, lph);
                landed++;
                if (++lslot == NS) { lslot = 0; lph ^= 1; }
            }
            if (pos >= NS) mbar_wait(bar_empty + slot * 8, ph);
        };
        const char* src = kc + kv_off + (POS_FIRST - POS_K) * TILE_BYTES;
#pragma unroll 1
        for (int pos = POS_FIRST; pos < POS_W2; pos++) {
            acquire(pos);
            const uint32_t dst = sb + OFF_RING + slot * TILE_BYTES, bar = bar_full + slot * 8;
            if (pos == POS_GO && leader) mbar_arrive(bar_x + B_GO);
            if (pos == POS_W1) {
                if (leader) {
                    if (cg < 7) {
                        mbar_expect_tx(bar, 448 * 32);
                        tma_2d(dst, &map_w1, 16 * fs, 0, bar);
                        tma_2d(dst + 224 * 32, &map_w1, 16 * fs, 224, bar);
                    } else {
                        mbar_arrive(bar);
                    }
                }
                src = vc + kv_off;
            } else {
                if (leader) {
                    if (pos >= POS_W2 - 2) {
                        const uint32_t bar2 = bar_x + B_VLAST + (pos - (POS_W2 - 2)) * 8;
                        mbar_expect_tx(bar, TILE_BYTES / 2);
                        mbar_expect_tx(bar2, TILE_BYTES / 2);
                        bulk_g2s(dst, src, TILE_BYTES / 2, bar);
                        bulk_g2s(dst + TILE_BYTES / 2, src + TILE_BYTES / 2, TILE_BYTES / 2, bar2);
                    } else {
                        mbar_expect_tx(bar, TILE_BYTES);
                        bulk_g2s(dst, src, TILE_BYTES, bar);
                    }
                }
                src += TILE_BYTES;
            }
            if (++slot == NS) { slot = 0; ph ^= 1; }
        }
        if (cg == 7) return;
        due += PACE_WGAP;
        acquire(POS_W2);
        if (leader) {
            mbar_expect_tx(bar_x + B_W2, 112 * 128);
            tma_2d(sb + OFF_RING + (POS_W2 % NS) * TILE_BYTES, &map_w2, 64 * cg, 112 * rho, bar_x + B_W2);
        }
        if (++slot == NS) { slot = 0; ph ^= 1; }
        const uint32_t wdst = sb + OFF_RING + (POS_WO % NS) * TILE_BYTES;
        acquire(POS_WO);
        if (leader) {
            mbar_expect_tx(bar_x + B_WO0, 4 * 4096);
#pragma unroll
            for (int i = 0; i < 4; i++) tma_2d(wdst + i * 4096, &map_wo, 64 * cg, 256 * rho + 32 * i, bar_x + B_WO0);
        }
        if (++slot == NS) { slot = 0; ph ^= 1; }
        acquire(POS_WO + 1);
        if (leader) {
            mbar_expect_tx(bar_x + B_WO1, 3 * 4096);
            mbar_expect_tx(bar_x + B_WO2, 4096);
#pragma unroll
            for (int i = 4; i < 8; i++)
                tma_2d(wdst + i * 4096, &map_wo, 64 * cg, 256 * rho + 32 * i, bar_x + (i < 7 ? B_WO1 : B_WO2));
        }
        return;
    }

    if (warp > 8) {
        const int mt = warp - 9;
        bar_sync(2, NTHREADS);
        if (cg == 7) return;
        mbar_wait(bar_x + B_GO, 0);
        const uint32_t tag = lds32u(sb + OFF_TG), par = tag & 1;
        const int ocol = 64 * cg + 16 * mt + (lane >> 2), ob = 2 * (lane & 3);
        unsigned long long* acc_p = &g_acc[(cg * 4 + mt) * 128 + lane];
        uint4* pbase = &g_pbuf[(cg * 4 + mt) * 512 + lane];
        __nv_bfloat16* out_p = out + ob * D_MODEL + ocol;
        asm volatile("" : "+l"(acc_p), "+l"(pbase), "+l"(out_p));
        auto bias_of = [&](int e) {
            return lds32f(sb + OFF_ST + (ob + (e & 1)) * 8 + 4) * __bfloat162float(b2[ocol + 8 * (e >> 1)]);
        };
        if (rho == 0) {
#pragma unroll
            for (int e = 0; e < 4; e++)
                asm volatile("red.relaxed.gpu.global.add.u64 [%0], %1;" :: "l"(acc_p + e * 32), "l"(to_fixed(bias_of(e))) : "memory");
        }
        uint32_t hf[7][2];
        {
            const unsigned long long* hsrc = &g_hbuf[(rho * 7 * 32 + lane) * 2];
            unsigned n = 0; bool ok;
            do {
                unsigned long long ha[7], hb[7];
#pragma unroll
                for (int i = 0; i < 7; i++) ld_pkt2(hsrc + i * 64, ha[i], hb[i]);
                ok = true;
#pragma unroll
                for (int i = 0; i < 7; i++) {
                    ok = ok && tag_of(ha[i]) == tag && tag_of(hb[i]) == tag;
                    hf[i][0] = pay_of(ha[i]); hf[i][1] = pay_of(hb[i]);
                }
                if (++n > SPIN_LIMIT) __trap();
            } while (!__all_sync(0xffffffffu, ok));
        }
        const int csw = 2 * mt + ((lane >> 3) & 1);
        float cc[4][4];
#pragma unroll
        for (int i = 0; i < 4; i++) { cc[i][0] = cc[i][1] = cc[i][2] = cc[i][3] = 0.f; }
        uint32_t os_l = sb + OFF_OS + lane * 16;
        asm volatile("" : "+r"(os_l));
        mbar_wait(bar_x + B_W2, 0);
        {
            const uint32_t wb = sb + OFF_RING + (POS_W2 % NS) * TILE_BYTES
                              + ((lane & 7) + ((lane >> 4) << 3)) * 128 + ((csw ^ (lane & 7)) << 4);
#pragma unroll
            for (int i = 0; i < 7; i++) {
                uint32_t a0, a1, a2, a3;
                ldsm_x4_t(wb + i * 2048, a0, a1, a2, a3);
                mma16816(cc[i & 3], a0, a1, a2, a3, hf[i][0], hf[i][1]);
            }
        }
        const int prow = 4 * ((lane & 7) >> 1) + (lane & 1) + ((((lane >> 4) ^ (lane >> 2)) & 1) << 1);
        uint32_t wb = sb + OFF_RING + (POS_WO % NS) * TILE_BYTES + prow * 128 + ((csw ^ (prow & 7)) << 4);
        asm volatile("" : "+r"(wb));
        uint32_t wf[16][4];
        uint4 of[8];
        auto load_w = [&](int lo, int hi) {
#pragma unroll
            for (int i = 0; i < 16; i++)
                if (i >= lo && i < hi) ldsm_x4_t(wb + i * 2048, wf[i][0], wf[i][1], wf[i][2], wf[i][3]);
        };
        auto mm = [&](int lo, int hi) {
#pragma unroll
            for (int i = 0; i < 16; i++)
                if (i >= lo && i < hi)
                    mma16816(cc[i & 3], wf[i][0], wf[i][1], wf[i][2], wf[i][3],
                             (i & 1) ? of[i >> 1].z : of[i >> 1].x, (i & 1) ? of[i >> 1].w : of[i >> 1].y);
        };
        mbar_wait(bar_x + B_WO0, 0);
        load_w(0, 8);
        mbar_wait(bar_x + B_WO1, 0);
        load_w(8, 14);
        const bool have2 = mbar_test(bar_x + B_WO2, 0);
        if (have2) load_w(14, 16);
        mbar_wait(bar_x + B_OS, 0);
#pragma unroll
        for (int i = 0; i < 8; i++) of[i] = lds128(os_l + i * 512);
        mm(0, 14);
        if (!have2) { mbar_wait(bar_x + B_WO2, 0); load_w(14, 16); }
        mm(14, 16);
        float res[4];
        unsigned long long tot[4], add[4];
#pragma unroll
        for (int e = 0; e < 4; e++) {
            res[e] = (cc[0][e] + cc[1][e]) + (cc[2][e] + cc[3][e]);
            add[e] = to_fixed(res[e]);
            asm volatile("atom.relaxed.gpu.global.add.u64 %0, [%1], %2;" : "=l"(tot[e]) : "l"(acc_p + e * 32), "l"(add[e]) : "memory");
        }
        st_v4(pbase + rho * 32, (__float_as_uint(res[0]) & ~1u) | par, (__float_as_uint(res[1]) & ~1u) | par,
                                (__float_as_uint(res[2]) & ~1u) | par, (__float_as_uint(res[3]) & ~1u) | par);
        uint32_t slow = 0;
#pragma unroll
        for (int e = 0; e < 4; e++) {
            tot[e] += add[e];
            const bool last = ((uint32_t)tot[e] & 31) == 17;
            const float val = (float)(long long)tot[e] * 0x1p-50f;
            const bool good = ((uint32_t)tot[e] & 0x3e0) == 0 && fabsf(val) >= 0x1p-24f;
            const __nv_bfloat16 r = __float2bfloat16_rn(val);
            if (last && good)
                asm volatile("st.global.u16 [%0], %1;" :: "l"(out_p + (e & 1) * D_MODEL + 8 * (e >> 1)), "h"(__bfloat16_as_ushort(r)) : "memory");
            if (last) asm volatile("st.relaxed.gpu.global.u64 [%0], %1;" :: "l"(acc_p + e * 32), "l"(0ull) : "memory");
            if (last && !good) slow |= 1u << e;
            if (e == 0 && last && cg == 0 && tid == 288)
                asm volatile("st.relaxed.gpu.global.u32 [%0], %1;" :: "l"(&g_epoch), "r"(tag) : "memory");
        }
        if (slow) {
            float r[4];
#pragma unroll
            for (int e = 0; e < 4; e++) r[e] = bias_of(e);
#pragma unroll 1
            for (int sr = 0; sr < 16; sr++) {
                uint32_t w[4]; unsigned m = 0;
                do {
                    asm volatile("ld.relaxed.gpu.global.v4.u32 {%0,%1,%2,%3}, [%4];"
                                 : "=r"(w[0]), "=r"(w[1]), "=r"(w[2]), "=r"(w[3]) : "l"(pbase + sr * 32) : "memory");
                    if (++m > SPIN_LIMIT) __trap();
                } while ((((w[0] ^ par) | (w[1] ^ par) | (w[2] ^ par) | (w[3] ^ par)) & 1) != 0);
#pragma unroll
                for (int e = 0; e < 4; e++) r[e] += __uint_as_float(w[e] & ~1u);
            }
#pragma unroll
            for (int e = 0; e < 4; e++)
                if ((slow >> e) & 1) out_p[(e & 1) * D_MODEL + 8 * (e >> 1)] = __float2bfloat16_rn(r[e]);
        }
        return;
    }

    const int g = lane >> 2, t = lane & 3;
    const uint32_t t_begin = gtime32();
    uint32_t epoch;
    asm volatile("ld.relaxed.gpu.global.u32 %0, [%1];" : "=r"(epoch) : "l"(&g_epoch) : "memory");
    uint32_t b1v = 0;
    if (cg < 7) b1v = *reinterpret_cast<const uint32_t*>(b1 + 16 * fs + 2 * (((tid >> 1) & 3) + 4 * (tid & 1)));

    {
        uint32_t xr[7], gr[7];
#pragma unroll
        for (int i = 0; i < 7; i++) {
            xr[i] = *reinterpret_cast<const uint32_t*>(x + warp * D_MODEL + 2 * (lane + 32 * i));
            gr[i] = *reinterpret_cast<const uint32_t*>(gw + 2 * (lane + 32 * i));
        }
        float sum = 0.f, gz = 0.f;
#pragma unroll
        for (int i = 0; i < 7; i++) {
            sts32(sb + OFF_XS + warp * XS_PITCH + (lane + 32 * i) * 4, xr[i]);
            sum += bf_lo(xr[i]) + bf_hi(xr[i]);
            gz += bf_round(bf_lo(xr[i]) * bf_lo(gr[i])) + bf_round(bf_hi(xr[i]) * bf_hi(gr[i]));
        }
#pragma unroll
        for (int o = 16; o; o >>= 1) { sum += __shfl_xor_sync(0xffffffffu, sum, o); gz += __shfl_xor_sync(0xffffffffu, gz, o); }
        const float mean = sum * (1.0f / D_MODEL);
        float var = 0.f;
#pragma unroll
        for (int i = 0; i < 7; i++) {
            const float d0 = bf_lo(xr[i]) - mean, d1 = bf_hi(xr[i]) - mean;
            var += d0 * d0 + d1 * d1;
        }
#pragma unroll
        for (int o = 16; o; o >>= 1) var += __shfl_xor_sync(0xffffffffu, var, o);
        const float den = bf_round(sqrtf(bf_round(bf_round(var * (1.0f / D_MODEL)) + 1e-5f)));
        const float mb = bf_round(mean);
#pragma unroll
        for (int i = 0; i < 7; i++) {
            sts32(sb + OFF_YS + warp * XS_PITCH + (lane + 32 * i) * 4,
                  pack_bf(__fdividef(bf_round(bf_lo(xr[i]) - mb), den), __fdividef(bf_round(bf_hi(xr[i]) - mb), den)));
        }
        if (lane == 0) {
            const float gt = bf_round(__fdividef(1.0f, 1.0f + __expf(-bf_round(gz))));
            sts64f(sb + OFF_ST + warp * 8, gt, bf_round(1.0f - gt));
        }
    }
    const uint32_t tag = (epoch + 1) ? epoch + 1 : 2;
    if (tid == 0) sts32(sb + OFF_TG, tag);
    bar_sync(2, NTHREADS);

    {
        const int mt = warp & 1, kq = warp >> 1;
        const int row = 112 * kq + (lane & 7) + ((lane >> 4) << 3);
        const uint32_t wa = sb + OFF_RING + row * 64 + (((2 * mt + ((lane >> 3) & 1)) ^ ((row >> 1) & 3)) << 4);
        const uint32_t xa = sb + OFF_XS + g * XS_PITCH + (112 * kq + 2 * t) * 2;
        uint32_t xb[7][2];
#pragma unroll
        for (int ks = 0; ks < 7; ks++) { xb[ks][0] = lds32u(xa + ks * 32); xb[ks][1] = lds32u(xa + ks * 32 + 16); }
        mbar_wait(bar_full + (kq >> 1) * 8, 0);
        float c0[4] = {0.f, 0.f, 0.f, 0.f}, c1[4] = {0.f, 0.f, 0.f, 0.f};
#pragma unroll
        for (int ks = 0; ks < 7; ks++) {
            uint32_t a0, a1, a2, a3;
            ldsm_x4_t(wa + ks * 1024, a0, a1, a2, a3);
            if (ks & 1) mma16816(c1, a0, a1, a2, a3, xb[ks][0], xb[ks][1]);
            else mma16816(c0, a0, a1, a2, a3, xb[ks][0], xb[ks][1]);
        }
        sts128f(sb + OFF_U + warp * 512 + lane * 16, c0[0] + c1[0], c0[1] + c1[1], c0[2] + c1[2], c0[3] + c1[3]);
        bar_sync(1, 256);
        if (tid < 128) {
            const int pb = tid >> 4, p = tid & 15;
            const uint32_t ra = sb + OFF_U + (p >> 3) * 512 + (4 * ((2 * p) & 7) + (pb >> 1)) * 16 + ((p >> 2) & 1) * 8 + (pb & 1) * 4;
            float v0 = 0.f, v1 = 0.f;
#pragma unroll
            for (int w = 0; w < 4; w++) { v0 += lds32f(ra + w * 1024); v1 += lds32f(ra + w * 1024 + 64); }
            st_pkt(&g_qbuf[(hkv * 8 + pb) * 256 + (c & 15) * 16 + p], pkt(pack_bf(v0, v1), tag));
        } else if (tid == 128) {
            mbar_arrive_n(bar_empty, 4);
            mbar_arrive_n(bar_empty + 8, 4);
        }
    }
    {
        const unsigned long long* qsrc = &g_qbuf[(hkv * 8 + b) * 256 + tid];
        unsigned long long v;
        unsigned n = 0;
        while ((int)(gtime32() - t_begin) < QPOLL_T && ++n < SPIN_LIMIT) { }
        n = 0;
        do { v = ld_pkt(qsrc); if (++n > SPIN_LIMIT) __trap(); } while (tag_of(v) != tag);
        sts32(sb + OFF_QS + tid * 4, pay_of(v));
    }
    bar_sync(1, 256);

    int slot = POS_K + (warp >> 2), ph = 0;
    const int r4 = lane >> 3, j8 = lane & 7;
    {
        float qr[2][4][8];
#pragma unroll
        for (int h = 0; h < 2; h++)
#pragma unroll
            for (int i = 0; i < 4; i++) {
                const uint4 u = lds128(sb + OFF_QS + h * 512 + i * 128 + j8 * 16);
                qr[h][i][0] = bf_lo(u.x); qr[h][i][1] = bf_hi(u.x); qr[h][i][2] = bf_lo(u.y); qr[h][i][3] = bf_hi(u.y);
                qr[h][i][4] = bf_lo(u.z); qr[h][i][5] = bf_hi(u.z); qr[h][i][6] = bf_lo(u.w); qr[h][i][7] = bf_hi(u.w);
            }
        const uint32_t koff = (8 * (warp & 3) + r4) * ROW_BYTES + j8 * 16;
        const uint32_t soff = sb + OFF_U + (8 * warp + 4 * (j8 >> 2) + r4) * 8 + ((j8 >> 1) & 1) * 4;
#pragma unroll 1
        for (int it = 0; it < 8; it++) {
            mbar_wait(bar_full + slot * 8, ph);
            const uint32_t base = sb + OFF_RING + slot * TILE_BYTES + koff;
            uint4 la[4], lb[4];
#pragma unroll
            for (int i = 0; i < 4; i++) { la[i] = lds128(base + i * 128); lb[i] = lds128(base + 4 * ROW_BYTES + i * 128); }
            float a0 = 0.f, a1 = 0.f, b0 = 0.f, b1_ = 0.f;
#pragma unroll
            for (int i = 0; i < 4; i++) {
                const uint32_t wa[4] = {la[i].x, la[i].y, la[i].z, la[i].w}, wb[4] = {lb[i].x, lb[i].y, lb[i].z, lb[i].w};
#pragma unroll
                for (int e = 0; e < 4; e++) {
                    const float al = bf_lo(wa[e]), ah = bf_hi(wa[e]), bl = bf_lo(wb[e]), bh = bf_hi(wb[e]);
                    a0 = fmaf(al, qr[0][i][2 * e], a0); a1 = fmaf(al, qr[1][i][2 * e], a1);
                    b0 = fmaf(bl, qr[0][i][2 * e], b0); b1_ = fmaf(bl, qr[1][i][2 * e], b1_);
                    a0 = fmaf(ah, qr[0][i][2 * e + 1], a0); a1 = fmaf(ah, qr[1][i][2 * e + 1], a1);
                    b0 = fmaf(bh, qr[0][i][2 * e + 1], b0); b1_ = fmaf(bh, qr[1][i][2 * e + 1], b1_);
                }
            }
            __syncwarp();
            if (lane == 0) mbar_arrive(bar_empty + slot * 8);
            const bool up = j8 & 4;
            const float k0 = (up ? b0 : a0) + __shfl_xor_sync(0xffffffffu, up ? a0 : b0, 4);
            const float k1 = (up ? b1_ : a1) + __shfl_xor_sync(0xffffffffu, up ? a1 : b1_, 4);
            const bool up2 = j8 & 2;
            float r = (up2 ? k1 : k0) + __shfl_xor_sync(0xffffffffu, up2 ? k0 : k1, 2);
            r += __shfl_xor_sync(0xffffffffu, r, 1);
            if ((lane & 1) == 0) sts32(soff + it * 512, __float_as_uint(r));
            slot += 2; if (slot >= NS) { slot -= NS; ph ^= 1; }
        }
        slot += 1; if (slot >= NS) { slot -= NS; ph ^= 1; }
    }
    if (warp < 4 && cg < 7) {
        const int row = 112 * warp + (lane & 7) + ((lane >> 4) << 3);
        const uint32_t wa = sb + OFF_RING + (POS_W1 % NS) * TILE_BYTES + row * 32 + ((((lane >> 3) & 1) ^ ((row >> 2) & 1)) << 4);
        const uint32_t ya = sb + OFF_YS + g * XS_PITCH + (112 * warp + 2 * t) * 2;
        mbar_wait(bar_full + (POS_W1 % NS) * 8, (POS_W1 / NS) & 1);
        float c0[4] = {0.f, 0.f, 0.f, 0.f};
#pragma unroll
        for (int ks = 0; ks < 7; ks++) {
            uint32_t a0, a1, a2, a3;
            ldsm_x4_t(wa + ks * 512, a0, a1, a2, a3);
            mma16816(c0, a0, a1, a2, a3, lds32u(ya + ks * 32), lds32u(ya + ks * 32 + 16));
        }
        sts128f(sb + OFF_HR + warp * 512 + lane * 16, c0[0], c0[1], c0[2], c0[3]);
    }
    bar_sync(1, 256);
    if (tid == 255) {
        mbar_wait(bar_full + (POS_W1 % NS) * 8, (POS_W1 / NS) & 1);
        mbar_arrive_n(bar_empty + (POS_W1 % NS) * 8, 4);
    }
    float own_m, own_l;
    {
        const uint4 p0 = lds128(sb + OFF_U + tid * 16);
        const float s00 = bf_round(__uint_as_float(p0.x)) * 0.0625f;
        const float s01 = bf_round(__uint_as_float(p0.y)) * 0.0625f;
        const float s10 = bf_round(__uint_as_float(p0.z)) * 0.0625f;
        const float s11 = bf_round(__uint_as_float(p0.w)) * 0.0625f;
        float m0 = fmaxf(s00, s10), m1 = fmaxf(s01, s11);
        __syncwarp();
#pragma unroll
        for (int o = 16; o; o >>= 1) {
            m0 = fmaxf(m0, __shfl_xor_sync(0xffffffffu, m0, o));
            m1 = fmaxf(m1, __shfl_xor_sync(0xffffffffu, m1, o));
        }
        if (lane == 0) sts64f(sb + OFF_WM + warp * 8, m0, m1);
        if (tid < 64 && cg < 7) {
            const int L = tid >> 1, hf = tid & 1, pb = L >> 2;
            const uint32_t ra = sb + OFF_HR + (4 * (2 * (L & 3)) + (pb >> 1)) * 16 + hf * 8 + (pb & 1) * 4;
            float v0 = 0.f, v1 = 0.f;
#pragma unroll
            for (int w = 0; w < 4; w++) { v0 += lds32f(ra + w * 512); v1 += lds32f(ra + w * 512 + 64); }
            const float omg = lds32f(sb + OFF_ST + pb * 8 + 4);
            v0 = bf_round(gelu_tanh(bf_round(bf_round(v0) + bf_lo(b1v)))) * omg;
            v1 = bf_round(gelu_tanh(bf_round(bf_round(v1) + bf_hi(b1v)))) * omg;
            st_pkt(&g_hbuf[(fs * 32 + L) * 2 + hf], pkt(pack_bf(v0, v1), tag));
        }
        bar_sync(1, 256);
#pragma unroll
        for (int w = 0; w < 4; w++) {
            const uint4 v = lds128(sb + OFF_WM + w * 16);
            m0 = fmaxf(m0, fmaxf(__uint_as_float(v.x), __uint_as_float(v.z)));
            m1 = fmaxf(m1, fmaxf(__uint_as_float(v.y), __uint_as_float(v.w)));
        }
        const float e00 = __expf(s00 - m0), e10 = __expf(s10 - m0), e01 = __expf(s01 - m1), e11 = __expf(s11 - m1);
        {
            const uint32_t pa = sb + OFF_PS + (tid >> 4) * 256 + (tid & 1) * 128 + ((tid >> 1) & 7) * 8;
            sts64f(pa, e00, e01);
            sts64f(pa + 64, e10, e11);
        }
        float l0 = e00 + e10, l1 = e01 + e11;
#pragma unroll
        for (int o = 16; o; o >>= 1) { l0 += __shfl_xor_sync(0xffffffffu, l0, o); l1 += __shfl_xor_sync(0xffffffffu, l1, o); }
        if (lane == 0) sts64f(sb + OFF_WS + warp * 8, l0, l1);
        bar_sync(1, 256);
        const int hh = lane >> 4;
        float l = 0.f;
#pragma unroll
        for (int w = 0; w < 8; w++) l += lds32f(sb + OFF_WS + w * 8 + hh * 4);
        own_m = hh ? m1 : m0; own_l = l;
        if ((tid & ~16) == 0)
            st_pkt2(&g_mlbuf[c * 4 + hh * 2], pkt(__float_as_uint(own_m), tag), pkt(__float_as_uint(l), tag));
    }
    float acc[2][8];
#pragma unroll
    for (int i = 0; i < 8; i++) { acc[0][i] = acc[1][i] = 0.f; }
    const int dq = warp & 3;
    const unsigned long long* msrc = &g_mlbuf[(c ^ 1) * 4 + (lane >> 4) * 2];
    unsigned long long pm = 0, pl = 0;
    float scale = 0.f;
    unsigned long long* const odst =
        &g_obuf[((((2 * hkv + (r4 >> 1)) * 2 + s) * 8 + 2 * dq + (j8 >> 2)) * 32 + b * 4 + 2 * (j8 & 1) + (r4 & 1)) * 2 + ((j8 >> 1) & 1)];
    {
        const uint32_t poff = sb + OFF_PS + (warp >> 2) * 256 + r4 * 64;
        const uint32_t voff = r4 * ROW_BYTES + dq * 128 + j8 * 16;
        auto rows = [&](const uint4 (&r)[4], const uint4& pa, const uint4& pb) {
#pragma unroll
            for (int j = 0; j < 4; j++) {
                const uint4& pp = (j & 2) ? pb : pa;
                const float p0 = __uint_as_float((j & 1) ? pp.z : pp.x), p1 = __uint_as_float((j & 1) ? pp.w : pp.y);
                const uint32_t wv[4] = {r[j].x, r[j].y, r[j].z, r[j].w};
#pragma unroll
                for (int e = 0; e < 4; e++) {
                    const float lo = bf_lo(wv[e]), hi = bf_hi(wv[e]);
                    acc[0][2 * e] = fmaf(lo, p0, acc[0][2 * e]); acc[1][2 * e] = fmaf(lo, p1, acc[1][2 * e]);
                    acc[0][2 * e + 1] = fmaf(hi, p0, acc[0][2 * e + 1]); acc[1][2 * e + 1] = fmaf(hi, p1, acc[1][2 * e + 1]);
                }
            }
        };
#pragma unroll 1
        for (int i = 0; i < 8; i++) {
            uint4 pf[4];
#pragma unroll
            for (int j = 0; j < 4; j++) pf[j] = lds128(poff + i * 512 + j * 16);
            if (i == PRE_IT && warp >= 4) {
                ld_pkt2(msrc, pm, pl);
                st_pkt(odst, (unsigned long long)((tag & 1) ^ 1));
            }
            if (i == PRE_IT + 3 && warp >= 4) {
                unsigned n = 0;
                while (tag_of(pm) != tag || tag_of(pl) != tag) { ld_pkt2(msrc, pm, pl); if (++n > SPIN_LIMIT) __trap(); }
                const float m_o = __uint_as_float(pay_of(pm)), l_o = __uint_as_float(pay_of(pl));
                const float m = fmaxf(own_m, m_o);
                const float e_s = __expf(own_m - m), e_o = __expf(m_o - m);
                scale = __fdividef(lds32f(sb + OFF_ST + b * 8) * e_s, e_s * own_l + e_o * l_o);
                __syncwarp();
            }
            mbar_wait(bar_full + slot * 8, ph);
            const uint32_t base = sb + OFF_RING + slot * TILE_BYTES + voff;
            uint4 ra[4], rb[4];
#pragma unroll
            for (int j = 0; j < 4; j++) ra[j] = lds128(base + j * 4 * ROW_BYTES);
            if (i == 7) {
                rows(ra, pf[0], pf[1]);
                mbar_wait(bar_x + B_VLAST + (warp >> 2) * 8, 0);
#pragma unroll
                for (int j = 0; j < 4; j++) rb[j] = lds128(base + (j + 4) * 4 * ROW_BYTES);
                rows(rb, pf[2], pf[3]);
                break;
            }
#pragma unroll
            for (int j = 0; j < 4; j++) rb[j] = lds128(base + (j + 4) * 4 * ROW_BYTES);
            rows(ra, pf[0], pf[1]);
            rows(rb, pf[2], pf[3]);
            __syncwarp();
            if (lane == 0) mbar_arrive(bar_empty + slot * 8);
            slot += 2; if (slot >= NS) { slot -= NS; ph ^= 1; }
        }
    }
    const bool up = lane & 16, up2 = lane & 8;
    float u[8], v[4];
#pragma unroll
    for (int e = 0; e < 8; e++) u[e] = (up ? acc[1][e] : acc[0][e]) + __shfl_xor_sync(0xffffffffu, up ? acc[0][e] : acc[1][e], 16);
#pragma unroll
    for (int e = 0; e < 4; e++) v[e] = (up2 ? u[e + 4] : u[e]) + __shfl_xor_sync(0xffffffffu, up2 ? u[e] : u[e + 4], 8);
    const uint32_t xa = sb + OFF_U + dq * 512 + lane * 16;
    if (warp >= 4) {
        bar_sync(5 + dq, 64);
        const uint4 o = lds128(xa);
        const float x0 = (v[0] + __uint_as_float(o.x)) * scale, x1 = (v[1] + __uint_as_float(o.y)) * scale;
        const float x2 = (v[2] + __uint_as_float(o.z)) * scale, x3 = (v[3] + __uint_as_float(o.w)) * scale;
        const bool sw = j8 & 1;
        const float v0 = sw ? x2 : x0, v1 = sw ? x3 : x1, v2 = sw ? x0 : x2, v3 = sw ? x1 : x3;
        const uint32_t w0 = (pack_bf(v0, v1) & 0xffff0000u) | (((__float_as_uint(v0) + 0x10000u) >> 16) & 0xfffeu) | (tag & 1);
        st_pkt(odst, pkt(w0, pack_bf(v2, v3)));
        return;
    }
    sts128f(xa, v[0], v[1], v[2], v[3]);
    bar_arrive(5 + dq, 64);
    if (cg == 7) return;
    {
        const uint32_t par = tag & 1;
        const unsigned long long* osrc = &g_obuf[((rho * 2 * 8 + 2 * dq) * 32 + lane) * 2];
        unsigned long long pa[4], pb[4];
        mbar_wait(bar_x + B_WO0, 0);
        ld_pkt2(osrc, pa[0], pb[0]);
        ld_pkt2(osrc + 512, pa[1], pb[1]);
        ld_pkt2(osrc + 64, pa[2], pb[2]);
        ld_pkt2(osrc + 512 + 64, pa[3], pb[3]);
        unsigned n = 0;
        while (true) {
            bool okk[4];
#pragma unroll
            for (int i = 0; i < 4; i++) okk[i] = ((((uint32_t)pa[i] ^ par) | ((uint32_t)pb[i] ^ par)) & 1) == 0;
            if (__all_sync(0xffffffffu, okk[0] && okk[1] && okk[2] && okk[3])) break;
            if (!okk[0]) ld_pkt2(osrc, pa[0], pb[0]);
            if (!okk[1]) ld_pkt2(osrc + 512, pa[1], pb[1]);
            if (!okk[2]) ld_pkt2(osrc + 64, pa[2], pb[2]);
            if (!okk[3]) ld_pkt2(osrc + 512 + 64, pa[3], pb[3]);
            if (++n > SPIN_LIMIT) __trap();
        }
#pragma unroll
        for (int i = 0; i < 2; i++) {
            sts128(sb + OFF_OS + lane * 16 + dq * 1024 + i * 512,
                   hadd2_bf((uint32_t)pa[2 * i] & ~1u, (uint32_t)pa[2 * i + 1] & ~1u),
                   hadd2_bf((uint32_t)(pa[2 * i] >> 32), (uint32_t)(pa[2 * i + 1] >> 32)),
                   hadd2_bf((uint32_t)pb[2 * i] & ~1u, (uint32_t)pb[2 * i + 1] & ~1u),
                   hadd2_bf((uint32_t)(pb[2 * i] >> 32), (uint32_t)(pb[2 * i + 1] >> 32)));
        }
        __syncwarp();
        if (lane == 0) mbar_arrive(bar_x + B_OS);
    }
}

typedef CUresult (*EncodeFn)(CUtensorMap*, CUtensorMapDataType, cuuint32_t, void*, const cuuint64_t*, const cuuint64_t*,
                             const cuuint32_t*, const cuuint32_t*, CUtensorMapInterleave, CUtensorMapSwizzle,
                             CUtensorMapL2promotion, CUtensorMapFloatOOBfill);

bool make_map(EncodeFn fn, CUtensorMap* m, const void* ptr, int cols, int rows, int box_cols, int box_rows,
              CUtensorMapSwizzle swz) {
    cuuint64_t dims[2] = {(cuuint64_t)cols, (cuuint64_t)rows};
    cuuint64_t strides[1] = {(cuuint64_t)cols * 2};
    cuuint32_t box[2] = {(cuuint32_t)box_cols, (cuuint32_t)box_rows};
    cuuint32_t es[2] = {1, 1};
    return fn(m, CU_TENSOR_MAP_DATA_TYPE_BFLOAT16, 2, const_cast<void*>(ptr), dims, strides, box, es,
              CU_TENSOR_MAP_INTERLEAVE_NONE, swz, CU_TENSOR_MAP_L2_PROMOTION_L2_128B,
              CU_TENSOR_MAP_FLOAT_OOB_FILL_NONE) == CUDA_SUCCESS;
}

}

extern "C" void kernel_launch(void* const* d_in, const int* in_sizes, int n_in, void* d_out, int out_size) {
    (void)in_sizes; (void)n_in; (void)out_size;
    static EncodeFn enc = nullptr;
    static int pace_ns = PACE_NS;
    if (!enc) {
        int dev = 0, khz = 0, bits = 0;
        if (cudaGetDevice(&dev) == cudaSuccess &&
            cudaDeviceGetAttribute(&khz, cudaDevAttrMemoryClockRate, dev) == cudaSuccess &&
            cudaDeviceGetAttribute(&bits, cudaDevAttrGlobalMemoryBusWidth, dev) == cudaSuccess && khz > 0 && bits > 0)
            pace_ns = (int)(PACE_NS * (2619000.0 * 5120.0) / ((double)khz * bits) + 0.5);
        void* fn = nullptr;
        cudaDriverEntryPointQueryResult qr;
        cudaGetDriverEntryPoint("cuTensorMapEncodeTiled", &fn, cudaEnableDefault, &qr);
        enc = (EncodeFn)fn;
        if (!enc) return;
        cudaFuncSetAttribute(fused_kernel, cudaFuncAttributeMaxDynamicSharedMemorySize, SMEM_BYTES);
    }
    CUtensorMap map_wq, map_w1, map_wo, map_w2;
    bool ok = make_map(enc, &map_wq, d_in[3], N_QCOL, D_MODEL, 32, 224, CU_TENSOR_MAP_SWIZZLE_64B);
    ok = ok && make_map(enc, &map_w1, d_in[6], FF, D_MODEL, 16, 224, CU_TENSOR_MAP_SWIZZLE_32B);
    ok = ok && make_map(enc, &map_wo, d_in[4], D_MODEL, N_QCOL, 64, 32, CU_TENSOR_MAP_SWIZZLE_128B);
    ok = ok && make_map(enc, &map_w2, d_in[8], D_MODEL, FF, 64, 112, CU_TENSOR_MAP_SWIZZLE_128B);
    if (!ok) return;

    cudaLaunchConfig_t cfg = {};
    cfg.gridDim = dim3(NCTA);
    cfg.blockDim = dim3(NTHREADS);
    cfg.dynamicSmemBytes = SMEM_BYTES;
    cfg.stream = cudaStreamPerThread;
    cudaLaunchAttribute at[1];
    at[0].id = cudaLaunchAttributeCooperative;
    at[0].val.cooperative = 1;
    cfg.attrs = at;
    cfg.numAttrs = 1;
    cudaLaunchKernelEx(&cfg, fused_kernel,
                       (const __nv_bfloat16*)d_in[0], (const char*)d_in[1], (const char*)d_in[2],
                       (const __nv_bfloat16*)d_in[7], (const __nv_bfloat16*)d_in[9],
                       (const __nv_bfloat16*)d_in[10], (__nv_bfloat16*)d_out, pace_ns, map_wq, map_w1, map_wo, map_w2);
}
```

```cpp
#include <cuda_runtime.h>
#include <cuda_bf16.h>
#include <cuda.h>
#include <stdint.h>

namespace {

constexpr int D_MODEL = 448;
constexpr int N_QCOL = 4096;
constexpr int SK = 4096;
constexpr int WIN = 1024;
constexpr int FF = 1792;
constexpr int NCTA = 128;
constexpr int NTHREADS = 416;

constexpr int ROW_BYTES = 512;
constexpr int TILE_ROWS = 32;
constexpr int TILE_BYTES = TILE_ROWS * ROW_BYTES;
constexpr int NS = 12;
constexpr int NT = 512 / TILE_ROWS;
constexpr int POS_K = 2, POS_W1 = POS_K + NT, POS_V = POS_W1 + 1, POS_W2 = POS_V + NT, POS_WO = POS_W2 + 1;
static_assert(POS_WO % NS + 2 <= NS, "wo tile must not wrap");
constexpr int POS_GO = POS_V + 6;

constexpr int POS_FIRST = 3;
constexpr int PACE_T0 = 650;
constexpr int PACE_NS = 654;
constexpr int PACE_WGAP = 800;
constexpr int DEPTH_LO = 2;
constexpr int DEPTH_HI = 10;
constexpr int DEPTH_W = 3;
constexpr int QPOLL_T = 4400;
constexpr int PRE_IT = 3;

constexpr int XS_PITCH = 912;

constexpr int OFF_RING = 0;
constexpr int OFF_U = NS * TILE_BYTES;
constexpr int OFF_XS = OFF_U + 8192;
constexpr int OFF_YS = OFF_U + 16384;
constexpr int OFF_OS = OFF_YS;
constexpr int OFF_PS = OFF_YS + 8192;
constexpr int OFF_QS = OFF_PS + 4096;
constexpr int OFF_HR = OFF_QS + 1024;
constexpr int OFF_ST = OFF_HR + 2048;
constexpr int OFF_WM = OFF_ST + 64;
constexpr int OFF_WS = OFF_WM + 64;
constexpr int OFF_TG = OFF_WS + 64;
constexpr int OFF_BAR = OFF_TG + 16;
constexpr int B_W2 = 0, B_WO0 = 8, B_WO1 = 16, B_WO2 = 24, B_GO = 32, B_VLAST = 40  , B_OS = 56;
constexpr int NBAR = 2 * NS + 8;
constexpr int SMEM_BYTES = OFF_BAR + NBAR * 8 + 1024;

constexpr unsigned SPIN_LIMIT = 1u << 22;

__device__ unsigned g_epoch;
__device__ __align__(128) unsigned long long g_qbuf[8 * 8 * 256];
__device__ __align__(128) unsigned long long g_hbuf[16 * 7 * 32 * 2];
__device__ __align__(128) unsigned long long g_mlbuf[NCTA * 4];
__device__ __align__(128) unsigned long long g_obuf[16 * 2 * 8 * 32 * 2];
__device__ __align__(128) uint4 g_pbuf[7 * 4 * 16 * 32];
__device__ __align__(128) unsigned long long g_acc[7 * 4 * 4 * 32];

__device__ __forceinline__ uint32_t gtime32() { uint32_t t; asm volatile("mov.u32 %0, %globaltimer_lo;" : "=r"(t)); return t; }
__device__ __forceinline__ void mbar_init(uint32_t bar, int cnt) {
    asm volatile("mbarrier.init.shared::cta.b64 [%0], %1;" :: "r"(bar), "r"(cnt) : "memory");
}
__device__ __forceinline__ void mbar_expect_tx(uint32_t bar, uint32_t bytes) {
    asm volatile("mbarrier.arrive.expect_tx.shared::cta.b64 _, [%0], %1;" :: "r"(bar), "r"(bytes) : "memory");
}
__device__ __forceinline__ void mbar_arrive(uint32_t bar) {
    asm volatile("mbarrier.arrive.shared::cta.b64 _, [%0];" :: "r"(bar) : "memory");
}
__device__ __forceinline__ void mbar_arrive_n(uint32_t bar, uint32_t n) {
    asm volatile("mbarrier.arrive.shared::cta.b64 _, [%0], %1;" :: "r"(bar), "r"(n) : "memory");
}
__device__ __forceinline__ bool mbar_try(uint32_t bar, uint32_t parity) {
    uint32_t ok;
    asm volatile("{\n.reg .pred p;\nmbarrier.try_wait.parity.shared::cta.b64 p, [%1], %2;\nselp.u32 %0, 1, 0, p;\n}"
                 : "=r"(ok) : "r"(bar), "r"(parity) : "memory");
    return ok != 0;
}
__device__ __forceinline__ bool mbar_test(uint32_t bar, uint32_t parity) {
    uint32_t ok;
    asm volatile("{\n.reg .pred p;\nmbarrier.test_wait.parity.shared::cta.b64 p, [%1], %2;\nselp.u32 %0, 1, 0, p;\n}"
                 : "=r"(ok) : "r"(bar), "r"(parity) : "memory");
    return ok != 0;
}
__device__ __forceinline__ void mbar_wait(uint32_t bar, uint32_t parity) {
    unsigned n = 0;
    while (!mbar_try(bar, parity)) { if (++n > SPIN_LIMIT) __trap(); }
}
constexpr unsigned long long POLICY_EVICT_FIRST = 0x12F0000000000000ull;
__device__ __forceinline__ void bulk_g2s(uint32_t dst, const void* src, uint32_t bytes, uint32_t bar) {
    asm volatile("cp.async.bulk.shared::cluster.global.mbarrier::complete_tx::bytes.L2::cache_hint [%0], [%1], %2, [%3], %4;"
                 :: "r"(dst), "l"(src), "r"(bytes), "r"(bar), "l"(POLICY_EVICT_FIRST) : "memory");
}
__device__ __forceinline__ void tma_2d(uint32_t dst, const CUtensorMap* map, int c0, int c1, uint32_t bar) {
    asm volatile("cp.async.bulk.tensor.2d.shared::cluster.global.mbarrier::complete_tx::bytes [%0], [%1, {%3, %4}], [%2];"
                 :: "r"(dst), "l"(map), "r"(bar), "r"(c0), "r"(c1) : "memory");
}
__device__ __forceinline__ void bar_sync(int id, int n) { asm volatile("bar.sync %0, %1;" :: "r"(id), "r"(n) : "memory"); }
__device__ __forceinline__ void bar_arrive(int id, int n) { asm volatile("bar.arrive %0, %1;" :: "r"(id), "r"(n) : "memory"); }
__device__ __forceinline__ bool elect_one() {
    uint32_t p;
    asm volatile("{\n.reg .pred p;\nelect.sync _|p, 0xffffffff;\nselp.u32 %0, 1, 0, p;\n}" : "=r"(p));
    return p != 0;
}
__device__ __forceinline__ uint4 lds128(uint32_t a) {
    uint4 v; asm volatile("ld.shared.v4.u32 {%0,%1,%2,%3}, [%4];" : "=r"(v.x), "=r"(v.y), "=r"(v.z), "=r"(v.w) : "r"(a) : "memory"); return v;
}
__device__ __forceinline__ void lds128x4(uint4 (&v)[4], uint32_t a) {
#pragma unroll
    for (int j = 0; j < 4; j++) v[j] = lds128(a + j * 4 * ROW_BYTES);
}
__device__ __forceinline__ float lds32f(uint32_t a) {
    float v; asm volatile("ld.shared.f32 %0, [%1];" : "=f"(v) : "r"(a) : "memory"); return v;
}
__device__ __forceinline__ uint32_t lds32u(uint32_t a) {
    uint32_t v; asm volatile("ld.shared.u32 %0, [%1];" : "=r"(v) : "r"(a) : "memory"); return v;
}
__device__ __forceinline__ void sts128(uint32_t a, uint32_t x, uint32_t y, uint32_t z, uint32_t w) {
    asm volatile("st.shared.v4.u32 [%0], {%1,%2,%3,%4};" :: "r"(a), "r"(x), "r"(y), "r"(z), "r"(w) : "memory");
}
__device__ __forceinline__ void sts128f(uint32_t a, float x, float y, float z, float w) {
    asm volatile("st.shared.v4.f32 [%0], {%1,%2,%3,%4};" :: "r"(a), "f"(x), "f"(y), "f"(z), "f"(w) : "memory");
}
__device__ __forceinline__ void sts64f(uint32_t a, float x, float y) {
    asm volatile("st.shared.v2.f32 [%0], {%1,%2};" :: "r"(a), "f"(x), "f"(y) : "memory");
}
__device__ __forceinline__ void sts32(uint32_t a, uint32_t x) {
    asm volatile("st.shared.u32 [%0], %1;" :: "r"(a), "r"(x) : "memory");
}
__device__ __forceinline__ void ldsm_x4_t(uint32_t a, uint32_t& r0, uint32_t& r1, uint32_t& r2, uint32_t& r3) {
    asm volatile("ldmatrix.sync.aligned.m8n8.x4.trans.shared.b16 {%0,%1,%2,%3}, [%4];"
                 : "=r"(r0), "=r"(r1), "=r"(r2), "=r"(r3) : "r"(a) : "memory");
}
__device__ __forceinline__ void mma16816(float (&c)[4], uint32_t a0, uint32_t a1, uint32_t a2, uint32_t a3,
                                         uint32_t b0, uint32_t b1) {
    asm volatile("mma.sync.aligned.m16n8k16.row.col.f32.bf16.bf16.f32 {%0,%1,%2,%3}, {%4,%5,%6,%7}, {%8,%9}, {%0,%1,%2,%3};"
                 : "+f"(c[0]), "+f"(c[1]), "+f"(c[2]), "+f"(c[3])
                 : "r"(a0), "r"(a1), "r"(a2), "r"(a3), "r"(b0), "r"(b1));
}
__device__ __forceinline__ float bf_lo(uint32_t v) { return __uint_as_float(v << 16); }
__device__ __forceinline__ float bf_hi(uint32_t v) { return __uint_as_float(v & 0xffff0000u); }
__device__ __forceinline__ float bf_round(float x) { return __bfloat162float(__float2bfloat16_rn(x)); }
__device__ __forceinline__ uint32_t pack_bf(float lo, float hi) {
    uint32_t r; asm("cvt.rn.bf16x2.f32 %0, %1, %2;" : "=r"(r) : "f"(hi), "f"(lo)); return r;
}
__device__ __forceinline__ uint32_t hadd2_bf(uint32_t a, uint32_t b) {
    uint32_t r; asm("add.rn.bf16x2 %0, %1, %2;" : "=r"(r) : "r"(a), "r"(b)); return r;
}
__device__ __forceinline__ unsigned long long pkt(uint32_t lo, uint32_t hi) { return ((unsigned long long)hi << 32) | lo; }
__device__ __forceinline__ uint32_t tag_of(unsigned long long v) { return (uint32_t)(v >> 32); }
__device__ __forceinline__ uint32_t pay_of(unsigned long long v) { return (uint32_t)v; }
__device__ __forceinline__ void st_pkt(unsigned long long* p, unsigned long long v) {
    asm volatile("st.relaxed.gpu.global.u64 [%0], %1;" :: "l"(p), "l"(v) : "memory");
}
__device__ __forceinline__ void st_pkt2(unsigned long long* p, unsigned long long a, unsigned long long b) {
    asm volatile("st.relaxed.gpu.global.v2.u64 [%0], {%1,%2};" :: "l"(p), "l"(a), "l"(b) : "memory");
}
__device__ __forceinline__ unsigned long long ld_pkt(const unsigned long long* p) {
    unsigned long long v; asm volatile("ld.relaxed.gpu.global.u64 %0, [%1];" : "=l"(v) : "l"(p) : "memory"); return v;
}
__device__ __forceinline__ void ld_pkt2(const unsigned long long* p, unsigned long long& a, unsigned long long& b) {
    asm volatile("ld.relaxed.gpu.global.v2.u64 {%0,%1}, [%2];" : "=l"(a), "=l"(b) : "l"(p) : "memory");
}
__device__ __forceinline__ void st_v4(uint4* p, uint32_t a, uint32_t b, uint32_t c, uint32_t d) {
    asm volatile("st.relaxed.gpu.global.v4.u32 [%0], {%1,%2,%3,%4};" :: "l"(p), "r"(a), "r"(b), "r"(c), "r"(d) : "memory");
}
__device__ __forceinline__ unsigned long long to_fixed(float v) {
    const bool ok = fabsf(v) < 256.0f;
    const long long q = __float2ll_rn((ok ? v : 0.0f) * 0x1p50f);
    return ((unsigned long long)q & ~1023ull) | (ok ? 1u : 33u);
}
__device__ __forceinline__ float gelu_tanh(float x) {
    const float u = 0.7978845608028654f * (x + 0.044715f * x * x * x);
    return 0.5f * x * (1.0f + tanhf(u));
}

__global__ void __launch_bounds__(NTHREADS, 1)
fused_kernel(const __nv_bfloat16* __restrict__ x, const char* __restrict__ kc, const char* __restrict__ vc,
             const __nv_bfloat16* __restrict__ b1, const __nv_bfloat16* __restrict__ b2,
             const __nv_bfloat16* __restrict__ gw, __nv_bfloat16* __restrict__ out, const int pace_ns,
             const __grid_constant__ CUtensorMap map_wq, const __grid_constant__ CUtensorMap map_w1,
             const __grid_constant__ CUtensorMap map_wo, const __grid_constant__ CUtensorMap map_w2) {
    extern __shared__ unsigned char smem_raw[];
    uint32_t sb = ((uint32_t)__cvta_generic_to_shared(smem_raw) + 1023u) & ~1023u;
    asm volatile("" : "+r"(sb));
    const int tid = threadIdx.x, warp = tid >> 5, lane = tid & 31;
    const int c = blockIdx.x;
    const int hkv = c >> 4, b = (c >> 1) & 7, s = c & 1;
    const int rho = c >> 3, cg = c & 7;
    const int fs = rho * 7 + cg;
    const uint32_t bar_full = sb + OFF_BAR, bar_empty = bar_full + NS * 8, bar_x = bar_empty + NS * 8;

    const size_t kv_off = ((size_t)(b * 8 + hkv) * SK + (SK - WIN) + s * 512) * ROW_BYTES;
    bool leader = false;
    if (warp == 8) {
        leader = elect_one();
        if (leader) {
#pragma unroll
            for (int i = 0; i < POS_FIRST; i++) mbar_init(bar_full + i * 8, 1);
            asm volatile("fence.mbarrier_init.release.cluster;" ::: "memory");
            mbar_expect_tx(bar_full, 224 * 64);
            tma_2d(sb + OFF_RING, &map_wq, 32 * c, 0, bar_full);
            mbar_expect_tx(bar_full + 8, 224 * 64);
            tma_2d(sb + OFF_RING + 224 * 64, &map_wq, 32 * c, 224, bar_full + 8);
#pragma unroll
            for (int i = POS_K; i < POS_FIRST; i++) {
                mbar_expect_tx(bar_full + i * 8, TILE_BYTES);
                bulk_g2s(sb + OFF_RING + i * TILE_BYTES, kc + kv_off + (i - POS_K) * TILE_BYTES, TILE_BYTES, bar_full + i * 8);
            }
        }
    }
    asm volatile("" ::: "memory");

    if (warp == 8) {
        if (leader) {
#pragma unroll
            for (int i = POS_FIRST; i < NS; i++) mbar_init(bar_full + i * 8, 1);
#pragma unroll
            for (int i = 0; i < NS; i++) mbar_init(bar_empty + i * 8, 4);
#pragma unroll
            for (int i = 0; i < 7; i++) mbar_init(bar_x + i * 8, 1);
            mbar_init(bar_x + B_OS, 4);
            asm volatile("fence.mbarrier_init.release.cluster;" ::: "memory");
        }
        __syncwarp();
        bar_arrive(2, NTHREADS);
        if (leader) {
            asm volatile("prefetch.tensormap [%0];" :: "l"(&map_w1) : "memory");
            asm volatile("prefetch.tensormap [%0];" :: "l"(&map_w2) : "memory");
            asm volatile("prefetch.tensormap [%0];" :: "l"(&map_wo) : "memory");
        }
        int slot = POS_FIRST, ph = 1;
        int landed = 0, lslot = 0, lph = 0;
        uint32_t due = gtime32() + PACE_T0;
        auto acquire = [&](int pos) {
            __syncwarp();
            unsigned n = 0;
            while ((int)(gtime32() - due) < 0 && ++n < SPIN_LIMIT) {
                if (landed < pos && landed < POS_W2 && mbar_test(bar_full + lslot * 8, lph)) {
                    landed++;
                    if (++lslot == NS) { lslot = 0; lph ^= 1; }
                }
                if (pos - landed < DEPTH_LO) break;
            }
            due += (pos >= POS_W2 - 1) ? (pace_ns * 11) >> 4 : pace_ns;
            const int depth = (pos >= POS_W2) ? DEPTH_W : DEPTH_HI;
            while (pos - landed >= depth && landed < POS_W2) {
                mbar_wait(bar_full + lslot * 8, lph);
                landed++;
                if (++lslot == NS) { lslot = 0; lph ^= 1; }
            }
            if (pos >= NS) mbar_wait(bar_empty + slot * 8, ph);
        };
        const char* src = kc + kv_off + (POS_FIRST - POS_K) * TILE_BYTES;
#pragma unroll 1
        for (int pos = POS_FIRST; pos < POS_W2; pos++) {
            acquire(pos);
            const uint32_t dst = sb + OFF_RING + slot * TILE_BYTES, bar = bar_full + slot * 8;
            if (pos == POS_GO && leader) mbar_arrive(bar_x + B_GO);
            if (pos == POS_W1) {
                if (leader) {
                    if (cg < 7) {
                        mbar_expect_tx(bar, 448 * 32);
                        tma_2d(dst, &map_w1, 16 * fs, 0, bar);
                        tma_2d(dst + 224 * 32, &map_w1, 16 * fs, 224, bar);
                    } else {
                        mbar_arrive(bar);
                    }
                }
                src = vc + kv_off;
            } else {
                if (leader) {
                    if (pos >= POS_W2 - 2) {
                        const uint32_t bar2 = bar_x + B_VLAST + (pos - (POS_W2 - 2)) * 8;
                        mbar_expect_tx(bar, TILE_BYTES / 2);
                        mbar_expect_tx(bar2, TILE_BYTES / 2);
                        bulk_g2s(dst, src, TILE_BYTES / 2, bar);
                        bulk_g2s(dst + TILE_BYTES / 2, src + TILE_BYTES / 2, TILE_BYTES / 2, bar2);
                    } else {
                        mbar_expect_tx(bar, TILE_BYTES);
                        bulk_g2s(dst, src, TILE_BYTES, bar);
                    }
                }
                src += TILE_BYTES;
            }
            if (++slot == NS) { slot = 0; ph ^= 1; }
        }
        if (cg == 7) return;
        due += PACE_WGAP;
        acquire(POS_W2);
        if (leader) {
            mbar_expect_tx(bar_x + B_W2, 112 * 128);
            tma_2d(sb + OFF_RING + (POS_W2 % NS) * TILE_BYTES, &map_w2, 64 * cg, 112 * rho, bar_x + B_W2);
        }
        if (++slot == NS) { slot = 0; ph ^= 1; }
        const uint32_t wdst = sb + OFF_RING + (POS_WO % NS) * TILE_BYTES;
        acquire(POS_WO);
        if (leader) {
            mbar_expect_tx(bar_x + B_WO0, 4 * 4096);
#pragma unroll
            for (int i = 0; i < 4; i++) tma_2d(wdst + i * 4096, &map_wo, 64 * cg, 256 * rho + 32 * i, bar_x + B_WO0);
        }
        if (++slot == NS) { slot = 0; ph ^= 1; }
        acquire(POS_WO + 1);
        if (leader) {
            mbar_expect_tx(bar_x + B_WO1, 3 * 4096);
            mbar_expect_tx(bar_x + B_WO2, 4096);
#pragma unroll
            for (int i = 4; i < 8; i++)
                tma_2d(wdst + i * 4096, &map_wo, 64 * cg, 256 * rho + 32 * i, bar_x + (i < 7 ? B_WO1 : B_WO2));
        }
        return;
    }

    if (warp > 8) {
        const int mt = warp - 9;
        bar_sync(2, NTHREADS);
        if (cg == 7) return;
        mbar_wait(bar_x + B_GO, 0);
        const uint32_t tag = lds32u(sb + OFF_TG), par = tag & 1;
        const int ocol = 64 * cg + 16 * mt + (lane >> 2), ob = 2 * (lane & 3);
        unsigned long long* acc_p = &g_acc[(cg * 4 + mt) * 128 + lane];
        uint4* pbase = &g_pbuf[(cg * 4 + mt) * 512 + lane];
        __nv_bfloat16* out_p = out + ob * D_MODEL + ocol;
        asm volatile("" : "+l"(acc_p), "+l"(pbase), "+l"(out_p));
        auto bias_of = [&](int e) {
            return lds32f(sb + OFF_ST + (ob + (e & 1)) * 8 + 4) * __bfloat162float(b2[ocol + 8 * (e >> 1)]);
        };
        if (rho == 0) {
#pragma unroll
            for (int e = 0; e < 4; e++)
                asm volatile("red.relaxed.gpu.global.add.u64 [%0], %1;" :: "l"(acc_p + e * 32), "l"(to_fixed(bias_of(e))) : "memory");
        }
        uint32_t hf[7][2];
        {
            const unsigned long long* hsrc = &g_hbuf[(rho * 7 * 32 + lane) * 2];
            unsigned n = 0; bool ok;
            do {
                unsigned long long ha[7], hb[7];
#pragma unroll
                for (int i = 0; i < 7; i++) ld_pkt2(hsrc + i * 64, ha[i], hb[i]);
                ok = true;
#pragma unroll
                for (int i = 0; i < 7; i++) {
                    ok = ok && tag_of(ha[i]) == tag && tag_of(hb[i]) == tag;
                    hf[i][0] = pay_of(ha[i]); hf[i][1] = pay_of(hb[i]);
                }
                if (++n > SPIN_LIMIT) __trap();
            } while (!__all_sync(0xffffffffu, ok));
        }
        const int csw = 2 * mt + ((lane >> 3) & 1);
        float cc[4][4];
#pragma unroll
        for (int i = 0; i < 4; i++) { cc[i][0] = cc[i][1] = cc[i][2] = cc[i][3] = 0.f; }
        uint32_t os_l = sb + OFF_OS + lane * 16;
        asm volatile("" : "+r"(os_l));
        mbar_wait(bar_x + B_W2, 0);
        {
            const uint32_t wb = sb + OFF_RING + (POS_W2 % NS) * TILE_BYTES
                              + ((lane & 7) + ((lane >> 4) << 3)) * 128 + ((csw ^ (lane & 7)) << 4);
#pragma unroll
            for (int i = 0; i < 7; i++) {
                uint32_t a0, a1, a2, a3;
                ldsm_x4_t(wb + i * 2048, a0, a1, a2, a3);
                mma16816(cc[i & 3], a0, a1, a2, a3, hf[i][0], hf[i][1]);
            }
        }
        const int prow = 4 * ((lane & 7) >> 1) + (lane & 1) + ((((lane >> 4) ^ (lane >> 2)) & 1) << 1);
        uint32_t wb = sb + OFF_RING + (POS_WO % NS) * TILE_BYTES + prow * 128 + ((csw ^ (prow & 7)) << 4);
        asm volatile("" : "+r"(wb));
        uint32_t wf[16][4];
        uint4 of[8];
        auto load_w = [&](int lo, int hi) {
#pragma unroll
            for (int i = 0; i < 16; i++)
                if (i >= lo && i < hi) ldsm_x4_t(wb + i * 2048, wf[i][0], wf[i][1], wf[i][2], wf[i][3]);
        };
        auto mm = [&](int lo, int hi) {
#pragma unroll
            for (int i = 0; i < 16; i++)
                if (i >= lo && i < hi)
                    mma16816(cc[i & 3], wf[i][0], wf[i][1], wf[i][2], wf[i][3],
                             (i & 1) ? of[i >> 1].z : of[i >> 1].x, (i & 1) ? of[i >> 1].w : of[i >> 1].y);
        };
        mbar_wait(bar_x + B_WO0, 0);
        load_w(0, 8);
        mbar_wait(bar_x + B_WO1, 0);
        load_w(8, 14);
        const bool have2 = mbar_test(bar_x + B_WO2, 0);
        if (have2) load_w(14, 16);
        mbar_wait(bar_x + B_OS, 0);
#pragma unroll
        for (int i = 0; i < 8; i++) of[i] = lds128(os_l + i * 512);
        mm(0, 14);
        if (!have2) { mbar_wait(bar_x + B_WO2, 0); load_w(14, 16); }
        mm(14, 16);
        float res[4];
        unsigned long long tot[4], add[4];
#pragma unroll
        for (int e = 0; e < 4; e++) {
            res[e] = (cc[0][e] + cc[1][e]) + (cc[2][e] + cc[3][e]);
            add[e] = to_fixed(res[e]);
            asm volatile("atom.relaxed.gpu.global.add.u64 %0, [%1], %2;" : "=l"(tot[e]) : "l"(acc_p + e * 32), "l"(add[e]) : "memory");
        }
        st_v4(pbase + rho * 32, (__float_as_uint(res[0]) & ~1u) | par, (__float_as_uint(res[1]) & ~1u) | par,
                                (__float_as_uint(res[2]) & ~1u) | par, (__float_as_uint(res[3]) & ~1u) | par);
        uint32_t slow = 0;
#pragma unroll
        for (int e = 0; e < 4; e++) {
            tot[e] += add[e];
            const bool last = ((uint32_t)tot[e] & 31) == 17;
            const float val = (float)(long long)tot[e] * 0x1p-50f;
            const bool good = ((uint32_t)tot[e] & 0x3e0) == 0 && fabsf(val) >= 0x1p-24f;
            const __nv_bfloat16 r = __float2bfloat16_rn(val);
            if (last && good)
                asm volatile("st.global.u16 [%0], %1;" :: "l"(out_p + (e & 1) * D_MODEL + 8 * (e >> 1)), "h"(__bfloat16_as_ushort(r)) : "memory");
            if (last) asm volatile("st.relaxed.gpu.global.u64 [%0], %1;" :: "l"(acc_p + e * 32), "l"(0ull) : "memory");
            if (last && !good) slow |= 1u << e;
            if (e == 0 && last && cg == 0 && tid == 288)
                asm volatile("st.relaxed.gpu.global.u32 [%0], %1;" :: "l"(&g_epoch), "r"(tag) : "memory");
        }
        if (slow) {
            float r[4];
#pragma unroll
            for (int e = 0; e < 4; e++) r[e] = bias_of(e);
#pragma unroll 1
            for (int sr = 0; sr < 16; sr++) {
                uint32_t w[4]; unsigned m = 0;
                do {
                    asm volatile("ld.relaxed.gpu.global.v4.u32 {%0,%1,%2,%3}, [%4];"
                                 : "=r"(w[0]), "=r"(w[1]), "=r"(w[2]), "=r"(w[3]) : "l"(pbase + sr * 32) : "memory");
                    if (++m > SPIN_LIMIT) __trap();
                } while ((((w[0] ^ par) | (w[1] ^ par) | (w[2] ^ par) | (w[3] ^ par)) & 1) != 0);
#pragma unroll
                for (int e = 0; e < 4; e++) r[e] += __uint_as_float(w[e] & ~1u);
            }
#pragma unroll
            for (int e = 0; e < 4; e++)
                if ((slow >> e) & 1) out_p[(e & 1) * D_MODEL + 8 * (e >> 1)] = __float2bfloat16_rn(r[e]);
        }
        return;
    }

    const int g = lane >> 2, t = lane & 3;
    const uint32_t t_begin = gtime32();
    uint32_t epoch;
    asm volatile("ld.relaxed.gpu.global.u32 %0, [%1];" : "=r"(epoch) : "l"(&g_epoch) : "memory");
    uint32_t b1v = 0;
    if (cg < 7) b1v = *reinterpret_cast<const uint32_t*>(b1 + 16 * fs + 2 * (((tid >> 1) & 3) + 4 * (tid & 1)));

    {
        uint32_t xr[7], gr[7];
#pragma unroll
        for (int i = 0; i < 7; i++) {
            xr[i] = *reinterpret_cast<const uint32_t*>(x + warp * D_MODEL + 2 * (lane + 32 * i));
            gr[i] = *reinterpret_cast<const uint32_t*>(gw + 2 * (lane + 32 * i));
        }
        float sum = 0.f, gz = 0.f;
#pragma unroll
        for (int i = 0; i < 7; i++) {
            sts32(sb + OFF_XS + warp * XS_PITCH + (lane + 32 * i) * 4, xr[i]);
            sum += bf_lo(xr[i]) + bf_hi(xr[i]);
            gz += bf_round(bf_lo(xr[i]) * bf_lo(gr[i])) + bf_round(bf_hi(xr[i]) * bf_hi(gr[i]));
        }
#pragma unroll
        for (int o = 16; o; o >>= 1) { sum += __shfl_xor_sync(0xffffffffu, sum, o); gz += __shfl_xor_sync(0xffffffffu, gz, o); }
        const float mean = sum * (1.0f / D_MODEL);
        float var = 0.f;
#pragma unroll
        for (int i = 0; i < 7; i++) {
            const float d0 = bf_lo(xr[i]) - mean, d1 = bf_hi(xr[i]) - mean;
            var += d0 * d0 + d1 * d1;
        }
#pragma unroll
        for (int o = 16; o; o >>= 1) var += __shfl_xor_sync(0xffffffffu, var, o);
        const float den = bf_round(sqrtf(bf_round(bf_round(var * (1.0f / D_MODEL)) + 1e-5f)));
        const float mb = bf_round(mean);
#pragma unroll
        for (int i = 0; i < 7; i++) {
            sts32(sb + OFF_YS + warp * XS_PITCH + (lane + 32 * i) * 4,
                  pack_bf(__fdividef(bf_round(bf_lo(xr[i]) - mb), den), __fdividef(bf_round(bf_hi(xr[i]) - mb), den)));
        }
        if (lane == 0) {
            const float gt = bf_round(__fdividef(1.0f, 1.0f + __expf(-bf_round(gz))));
            sts64f(sb + OFF_ST + warp * 8, gt, bf_round(1.0f - gt));
        }
    }
    const uint32_t tag = (epoch + 1) ? epoch + 1 : 2;
    if (tid == 0) sts32(sb + OFF_TG, tag);
    bar_sync(2, NTHREADS);

    {
        const int mt = warp & 1, kq = warp >> 1;
        const int row = 112 * kq + (lane & 7) + ((lane >> 4) << 3);
        const uint32_t wa = sb + OFF_RING + row * 64 + (((2 * mt + ((lane >> 3) & 1)) ^ ((row >> 1) & 3)) << 4);
        const uint32_t xa = sb + OFF_XS + g * XS_PITCH + (112 * kq + 2 * t) * 2;
        uint32_t xb[7][2];
#pragma unroll
        for (int ks = 0; ks < 7; ks++) { xb[ks][0] = lds32u(xa + ks * 32); xb[ks][1] = lds32u(xa + ks * 32 + 16); }
        mbar_wait(bar_full + (kq >> 1) * 8, 0);
        float c0[4] = {0.f, 0.f, 0.f, 0.f}, c1[4] = {0.f, 0.f, 0.f, 0.f};
#pragma unroll
        for (int ks = 0; ks < 7; ks++) {
            uint32_t a0, a1, a2, a3;
            ldsm_x4_t(wa + ks * 1024, a0, a1, a2, a3);
            if (ks & 1) mma16816(c1, a0, a1, a2, a3, xb[ks][0], xb[ks][1]);
            else mma16816(c0, a0, a1, a2, a3, xb[ks][0], xb[ks][1]);
        }
        sts128f(sb + OFF_U + warp * 512 + lane * 16, c0[0] + c1[0], c0[1] + c1[1], c0[2] + c1[2], c0[3] + c1[3]);
        bar_sync(1, 256);
        if (tid < 128) {
            const int pb = tid >> 4, p = tid & 15;
            const uint32_t ra = sb + OFF_U + (p >> 3) * 512 + (4 * ((2 * p) & 7) + (pb >> 1)) * 16 + ((p >> 2) & 1) * 8 + (pb & 1) * 4;
            float v0 = 0.f, v1 = 0.f;
#pragma unroll
            for (int w = 0; w < 4; w++) { v0 += lds32f(ra + w * 1024); v1 += lds32f(ra + w * 1024 + 64); }
            st_pkt(&g_qbuf[(hkv * 8 + pb) * 256 + (c & 15) * 16 + p], pkt(pack_bf(v0, v1), tag));
        } else if (tid == 128) {
            mbar_arrive_n(bar_empty, 4);
            mbar_arrive_n(bar_empty + 8, 4);
        }
    }
    {
        const unsigned long long* qsrc = &g_qbuf[(hkv * 8 + b) * 256 + tid];
        unsigned long long v;
        unsigned n = 0;
        while ((int)(gtime32() - t_begin) < QPOLL_T && ++n < SPIN_LIMIT) { }
        n = 0;
        do { v = ld_pkt(qsrc); if (++n > SPIN_LIMIT) __trap(); } while (tag_of(v) != tag);
        sts32(sb + OFF_QS + tid * 4, pay_of(v));
    }
    bar_sync(1, 256);

    int slot = POS_K + (warp >> 2), ph = 0;
    const int r4 = lane >> 3, j8 = lane & 7;
    {
        float qr[2][4][8];
#pragma unroll
        for (int h = 0; h < 2; h++)
#pragma unroll
            for (int i = 0; i < 4; i++) {
                const uint4 u = lds128(sb + OFF_QS + h * 512 + i * 128 + j8 * 16);
                qr[h][i][0] = bf_lo(u.x); qr[h][i][1] = bf_hi(u.x); qr[h][i][2] = bf_lo(u.y); qr[h][i][3] = bf_hi(u.y);
                qr[h][i][4] = bf_lo(u.z); qr[h][i][5] = bf_hi(u.z); qr[h][i][6] = bf_lo(u.w); qr[h][i][7] = bf_hi(u.w);
            }
        const uint32_t koff = (8 * (warp & 3) + r4) * ROW_BYTES + j8 * 16;
        const uint32_t soff = sb + OFF_U + (8 * warp + 4 * (j8 >> 2) + r4) * 8 + ((j8 >> 1) & 1) * 4;
#pragma unroll 1
        for (int it = 0; it < 8; it++) {
            mbar_wait(bar_full + slot * 8, ph);
            const uint32_t base = sb + OFF_RING + slot * TILE_BYTES + koff;
            uint4 la[4], lb[4];
#pragma unroll
            for (int i = 0; i < 4; i++) { la[i] = lds128(base + i * 128); lb[i] = lds128(base + 4 * ROW_BYTES + i * 128); }
            float a0 = 0.f, a1 = 0.f, b0 = 0.f, b1_ = 0.f;
#pragma unroll
            for (int i = 0; i < 4; i++) {
                const uint32_t wa[4] = {la[i].x, la[i].y, la[i].z, la[i].w}, wb[4] = {lb[i].x, lb[i].y, lb[i].z, lb[i].w};
#pragma unroll
                for (int e = 0; e < 4; e++) {
                    const float al = bf_lo(wa[e]), ah = bf_hi(wa[e]), bl = bf_lo(wb[e]), bh = bf_hi(wb[e]);
                    a0 = fmaf(al, qr[0][i][2 * e], a0); a1 = fmaf(al, qr[1][i][2 * e], a1);
                    b0 = fmaf(bl, qr[0][i][2 * e], b0); b1_ = fmaf(bl, qr[1][i][2 * e], b1_);
                    a0 = fmaf(ah, qr[0][i][2 * e + 1], a0); a1 = fmaf(ah, qr[1][i][2 * e + 1], a1);
                    b0 = fmaf(bh, qr[0][i][2 * e + 1], b0); b1_ = fmaf(bh, qr[1][i][2 * e + 1], b1_);
                }
            }
            __syncwarp();
            if (lane == 0) mbar_arrive(bar_empty + slot * 8);
            const bool up = j8 & 4;
            const float k0 = (up ? b0 : a0) + __shfl_xor_sync(0xffffffffu, up ? a0 : b0, 4);
            const float k1 = (up ? b1_ : a1) + __shfl_xor_sync(0xffffffffu, up ? a1 : b1_, 4);
            const bool up2 = j8 & 2;
            float r = (up2 ? k1 : k0) + __shfl_xor_sync(0xffffffffu, up2 ? k0 : k1, 2);
            r += __shfl_xor_sync(0xffffffffu, r, 1);
            if ((lane & 1) == 0) sts32(soff + it * 512, __float_as_uint(r));
            slot += 2; if (slot >= NS) { slot -= NS; ph ^= 1; }
        }
        slot += 1; if (slot >= NS) { slot -= NS; ph ^= 1; }
    }
    if (warp < 4 && cg < 7) {
        const int row = 112 * warp + (lane & 7) + ((lane >> 4) << 3);
        const uint32_t wa = sb + OFF_RING + (POS_W1 % NS) * TILE_BYTES + row * 32 + ((((lane >> 3) & 1) ^ ((row >> 2) & 1)) << 4);
        const uint32_t ya = sb + OFF_YS + g * XS_PITCH + (112 * warp + 2 * t) * 2;
        mbar_wait(bar_full + (POS_W1 % NS) * 8, (POS_W1 / NS) & 1);
        float c0[4] = {0.f, 0.f, 0.f, 0.f};
#pragma unroll
        for (int ks = 0; ks < 7; ks++) {
            uint32_t a0, a1, a2, a3;
            ldsm_x4_t(wa + ks * 512, a0, a1, a2, a3);
            mma16816(c0, a0, a1, a2, a3, lds32u(ya + ks * 32), lds32u(ya + ks * 32 + 16));
        }
        sts128f(sb + OFF_HR + warp * 512 + lane * 16, c0[0], c0[1], c0[2], c0[3]);
    }
    bar_sync(1, 256);
    if (tid == 255) {
        mbar_wait(bar_full + (POS_W1 % NS) * 8, (POS_W1 / NS) & 1);
        mbar_arrive_n(bar_empty + (POS_W1 % NS) * 8, 4);
    }
    float own_m, own_l;
    {
        const uint4 p0 = lds128(sb + OFF_U + tid * 16);
        const float s00 = bf_round(__uint_as_float(p0.x)) * 0.0625f;
        const float s01 = bf_round(__uint_as_float(p0.y)) * 0.0625f;
        const float s10 = bf_round(__uint_as_float(p0.z)) * 0.0625f;
        const float s11 = bf_round(__uint_as_float(p0.w)) * 0.0625f;
        float m0 = fmaxf(s00, s10), m1 = fmaxf(s01, s11);
        __syncwarp();
#pragma unroll
        for (int o = 16; o; o >>= 1) {
            m0 = fmaxf(m0, __shfl_xor_sync(0xffffffffu, m0, o));
            m1 = fmaxf(m1, __shfl_xor_sync(0xffffffffu, m1, o));
        }
        if (lane == 0) sts64f(sb + OFF_WM + warp * 8, m0, m1);
        if (tid < 64 && cg < 7) {
            const int L = tid >> 1, hf = tid & 1, pb = L >> 2;
            const uint32_t ra = sb + OFF_HR + (4 * (2 * (L & 3)) + (pb >> 1)) * 16 + hf * 8 + (pb & 1) * 4;
            float v0 = 0.f, v1 = 0.f;
#pragma unroll
            for (int w = 0; w < 4; w++) { v0 += lds32f(ra + w * 512); v1 += lds32f(ra + w * 512 + 64); }
            const float omg = lds32f(sb + OFF_ST + pb * 8 + 4);
            v0 = bf_round(gelu_tanh(bf_round(bf_round(v0) + bf_lo(b1v)))) * omg;
            v1 = bf_round(gelu_tanh(bf_round(bf_round(v1) + bf_hi(b1v)))) * omg;
            st_pkt(&g_hbuf[(fs * 32 + L) * 2 + hf], pkt(pack_bf(v0, v1), tag));
        }
        bar_sync(1, 256);
#pragma unroll
        for (int w = 0; w < 4; w++) {
            const uint4 v = lds128(sb + OFF_WM + w * 16);
            m0 = fmaxf(m0, fmaxf(__uint_as_float(v.x), __uint_as_float(v.z)));
            m1 = fmaxf(m1, fmaxf(__uint_as_float(v.y), __uint_as_float(v.w)));
        }
        const float e00 = __expf(s00 - m0), e10 = __expf(s10 - m0), e01 = __expf(s01 - m1), e11 = __expf(s11 - m1);
        {
            const uint32_t pa = sb + OFF_PS + (tid >> 4) * 256 + (tid & 1) * 128 + ((tid >> 1) & 7) * 8;
            sts64f(pa, e00, e01);
            sts64f(pa + 64, e10, e11);
        }
        float l0 = e00 + e10, l1 = e01 + e11;
#pragma unroll
        for (int o = 16; o; o >>= 1) { l0 += __shfl_xor_sync(0xffffffffu, l0, o); l1 += __shfl_xor_sync(0xffffffffu, l1, o); }
        if (lane == 0) sts64f(sb + OFF_WS + warp * 8, l0, l1);
        bar_sync(1, 256);
        const int hh = lane >> 4;
        float l = 0.f;
#pragma unroll
        for (int w = 0; w < 8; w++) l += lds32f(sb + OFF_WS + w * 8 + hh * 4);
        own_m = hh ? m1 : m0; own_l = l;
        if ((tid & ~16) == 0)
            st_pkt2(&g_mlbuf[c * 4 + hh * 2], pkt(__float_as_uint(own_m), tag), pkt(__float_as_uint(l), tag));
    }
    float acc[2][8];
#pragma unroll
    for (int i = 0; i < 8; i++) { acc[0][i] = acc[1][i] = 0.f; }
    const int dq = warp & 3;
    const unsigned long long* msrc = &g_mlbuf[(c ^ 1) * 4 + (lane >> 4) * 2];
    unsigned long long pm = 0, pl = 0;
    float scale = 0.f;
    unsigned long long* const odst =
        &g_obuf[((((2 * hkv + (r4 >> 1)) * 2 + s) * 8 + 2 * dq + (j8 >> 2)) * 32 + b * 4 + 2 * (j8 & 1) + (r4 & 1)) * 2 + ((j8 >> 1) & 1)];
    {
        const uint32_t poff = sb + OFF_PS + (warp >> 2) * 256 + r4 * 64;
        const uint32_t voff = r4 * ROW_BYTES + dq * 128 + j8 * 16;
        auto rows = [&](const uint4 (&r)[4], const uint4& pa, const uint4& pb) {
#pragma unroll
            for (int j = 0; j < 4; j++) {
                const uint4& pp = (j & 2) ? pb : pa;
                const float p0 = __uint_as_float((j & 1) ? pp.z : pp.x), p1 = __uint_as_float((j & 1) ? pp.w : pp.y);
                const uint32_t wv[4] = {r[j].x, r[j].y, r[j].z, r[j].w};
#pragma unroll
                for (int e = 0; e < 4; e++) {
                    const float lo = bf_lo(wv[e]), hi = bf_hi(wv[e]);
                    acc[0][2 * e] = fmaf(lo, p0, acc[0][2 * e]); acc[1][2 * e] = fmaf(lo, p1, acc[1][2 * e]);
                    acc[0][2 * e + 1] = fmaf(hi, p0, acc[0][2 * e + 1]); acc[1][2 * e + 1] = fmaf(hi, p1, acc[1][2 * e + 1]);
                }
            }
        };
#pragma unroll 1
        for (int i = 0; i < 8; i++) {
            uint4 pf[4];
#pragma unroll
            for (int j = 0; j < 4; j++) pf[j] = lds128(poff + i * 512 + j * 16);
            if (i == PRE_IT && warp >= 4) {
                ld_pkt2(msrc, pm, pl);
                st_pkt(odst, (unsigned long long)((tag & 1) ^ 1));
            }
            if (i == PRE_IT + 3 && warp >= 4) {
                unsigned n = 0;
                while (tag_of(pm) != tag || tag_of(pl) != tag) { ld_pkt2(msrc, pm, pl); if (++n > SPIN_LIMIT) __trap(); }
                const float m_o = __uint_as_float(pay_of(pm)), l_o = __uint_as_float(pay_of(pl));
                const float m = fmaxf(own_m, m_o);
                const float e_s = __expf(own_m - m), e_o = __expf(m_o - m);
                scale = __fdividef(lds32f(sb + OFF_ST + b * 8) * e_s, e_s * own_l + e_o * l_o);
                __syncwarp();
            }
            mbar_wait(bar_full + slot * 8, ph);
            const uint32_t base = sb + OFF_RING + slot * TILE_BYTES + voff;
            uint4 ra[4], rb[4];
            lds128x4(ra, base);
            if (i == 7) {
                rows(ra, pf[0], pf[1]);
                mbar_wait(bar_x + B_VLAST + (warp >> 2) * 8, 0);
                lds128x4(rb, base + TILE_BYTES / 2);
                rows(rb, pf[2], pf[3]);
                break;
            }
            lds128x4(rb, base + TILE_BYTES / 2);
            rows(ra, pf[0], pf[1]);
            rows(rb, pf[2], pf[3]);
            __syncwarp();
            if (lane == 0) mbar_arrive(bar_empty + slot * 8);
            slot += 2; if (slot >= NS) { slot -= NS; ph ^= 1; }
        }
    }
    const bool up = lane & 16, up2 = lane & 8;
    float u[8], v[4];
#pragma unroll
    for (int e = 0; e < 8; e++) u[e] = (up ? acc[1][e] : acc[0][e]) + __shfl_xor_sync(0xffffffffu, up ? acc[0][e] : acc[1][e], 16);
#pragma unroll
    for (int e = 0; e < 4; e++) v[e] = (up2 ? u[e + 4] : u[e]) + __shfl_xor_sync(0xffffffffu, up2 ? u[e] : u[e + 4], 8);
    const uint32_t xa = sb + OFF_U + dq * 512 + lane * 16;
    if (warp >= 4) {
        bar_sync(5 + dq, 64);
        const uint4 o = lds128(xa);
        const float x0 = (v[0] + __uint_as_float(o.x)) * scale, x1 = (v[1] + __uint_as_float(o.y)) * scale;
        const float x2 = (v[2] + __uint_as_float(o.z)) * scale, x3 = (v[3] + __uint_as_float(o.w)) * scale;
        const bool sw = j8 & 1;
        const float v0 = sw ? x2 : x0, v1 = sw ? x3 : x1, v2 = sw ? x0 : x2, v3 = sw ? x1 : x3;
        const uint32_t w0 = (pack_bf(v0, v1) & 0xffff0000u) | (((__float_as_uint(v0) + 0x10000u) >> 16) & 0xfffeu) | (tag & 1);
        st_pkt(odst, pkt(w0, pack_bf(v2, v3)));
        return;
    }
    sts128f(xa, v[0], v[1], v[2], v[3]);
    bar_arrive(5 + dq, 64);
    if (cg == 7) return;
    {
        const uint32_t par = tag & 1;
        const unsigned long long* osrc = &g_obuf[((rho * 2 * 8 + 2 * dq) * 32 + lane) * 2];
        uint32_t os_w = sb + OFF_OS + lane * 16 + dq * 1024;
        asm volatile("" : "+l"(osrc), "+r"(os_w));
        unsigned long long pa[4], pb[4];
        mbar_wait(bar_x + B_WO0, 0);
        ld_pkt2(osrc, pa[0], pb[0]);
        ld_pkt2(osrc + 512, pa[1], pb[1]);
        ld_pkt2(osrc + 64, pa[2], pb[2]);
        ld_pkt2(osrc + 512 + 64, pa[3], pb[3]);
        unsigned n = 0;
        while (true) {
            bool okk[4];
#pragma unroll
            for (int i = 0; i < 4; i++) okk[i] = ((((uint32_t)pa[i] ^ par) | ((uint32_t)pb[i] ^ par)) & 1) == 0;
            if (__all_sync(0xffffffffu, okk[0] && okk[1] && okk[2] && okk[3])) break;
            if (!okk[0]) ld_pkt2(osrc, pa[0], pb[0]);
            if (!okk[1]) ld_pkt2(osrc + 512, pa[1], pb[1]);
            if (!okk[2]) ld_pkt2(osrc + 64, pa[2], pb[2]);
            if (!okk[3]) ld_pkt2(osrc + 512 + 64, pa[3], pb[3]);
            if (++n > SPIN_LIMIT) __trap();
        }
#pragma unroll
        for (int i = 0; i < 2; i++) {
            sts128(os_w + i * 512,
                   hadd2_bf((uint32_t)pa[2 * i] & ~1u, (uint32_t)pa[2 * i + 1] & ~1u),
                   hadd2_bf((uint32_t)(pa[2 * i] >> 32), (uint32_t)(pa[2 * i + 1] >> 32)),
                   hadd2_bf((uint32_t)pb[2 * i] & ~1u, (uint32_t)pb[2 * i + 1] & ~1u),
                   hadd2_bf((uint32_t)(pb[2 * i] >> 32), (uint32_t)(pb[2 * i + 1] >> 32)));
        }
        __syncwarp();
        if (lane == 0) mbar_arrive(bar_x + B_OS);
    }
}

typedef CUresult (*EncodeFn)(CUtensorMap*, CUtensorMapDataType, cuuint32_t, void*, const cuuint64_t*, const cuuint64_t*,
                             const cuuint32_t*, const cuuint32_t*, CUtensorMapInterleave, CUtensorMapSwizzle,
                             CUtensorMapL2promotion, CUtensorMapFloatOOBfill);

bool make_map(EncodeFn fn, CUtensorMap* m, const void* ptr, int cols, int rows, int box_cols, int box_rows,
              CUtensorMapSwizzle swz) {
    cuuint64_t dims[2] = {(cuuint64_t)cols, (cuuint64_t)rows};
    cuuint64_t strides[1] = {(cuuint64_t)cols * 2};
    cuuint32_t box[2] = {(cuuint32_t)box_cols, (cuuint32_t)box_rows};
    cuuint32_t es[2] = {1, 1};
    return fn(m, CU_TENSOR_MAP_DATA_TYPE_BFLOAT16, 2, const_cast<void*>(ptr), dims, strides, box, es,
              CU_TENSOR_MAP_INTERLEAVE_NONE, swz, CU_TENSOR_MAP_L2_PROMOTION_L2_128B,
              CU_TENSOR_MAP_FLOAT_OOB_FILL_NONE) == CUDA_SUCCESS;
}

}

extern "C" void kernel_launch(void* const* d_in, const int* in_sizes, int n_in, void* d_out, int out_size) {
    (void)in_sizes; (void)n_in; (void)out_size;
    static EncodeFn enc = nullptr;
    static int pace_ns = PACE_NS;
    if (!enc) {
        int dev = 0, khz = 0, bits = 0;
        if (cudaGetDevice(&dev) == cudaSuccess &&
            cudaDeviceGetAttribute(&khz, cudaDevAttrMemoryClockRate, dev) == cudaSuccess &&
            cudaDeviceGetAttribute(&bits, cudaDevAttrGlobalMemoryBusWidth, dev) == cudaSuccess && khz > 0 && bits > 0)
            pace_ns = (int)(PACE_NS * (2619000.0 * 5120.0) / ((double)khz * bits) + 0.5);
        void* fn = nullptr;
        cudaDriverEntryPointQueryResult qr;
        cudaGetDriverEntryPoint("cuTensorMapEncodeTiled", &fn, cudaEnableDefault, &qr);
        enc = (EncodeFn)fn;
        if (!enc) return;
        cudaFuncSetAttribute(fused_kernel, cudaFuncAttributeMaxDynamicSharedMemorySize, SMEM_BYTES);
    }
    CUtensorMap map_wq, map_w1, map_wo, map_w2;
    bool ok = make_map(enc, &map_wq, d_in[3], N_QCOL, D_MODEL, 32, 224, CU_TENSOR_MAP_SWIZZLE_64B);
    ok = ok && make_map(enc, &map_w1, d_in[6], FF, D_MODEL, 16, 224, CU_TENSOR_MAP_SWIZZLE_32B);
    ok = ok && make_map(enc, &map_wo, d_in[4], D_MODEL, N_QCOL, 64, 32, CU_TENSOR_MAP_SWIZZLE_128B);
    ok = ok && make_map(enc, &map_w2, d_in[8], D_MODEL, FF, 64, 112, CU_TENSOR_MAP_SWIZZLE_128B);
    if (!ok) return;

    cudaLaunchConfig_t cfg = {};
    cfg.gridDim = dim3(NCTA);
    cfg.blockDim = dim3(NTHREADS);
    cfg.dynamicSmemBytes = SMEM_BYTES;
    cfg.stream = cudaStreamPerThread;
    cudaLaunchAttribute at[1];
    at[0].id = cudaLaunchAttributeCooperative;
    at[0].val.cooperative = 1;
    cfg.attrs = at;
    cfg.numAttrs = 1;
    cudaLaunchKernelEx(&cfg, fused_kernel,
                       (const __nv_bfloat16*)d_in[0], (const char*)d_in[1], (const char*)d_in[2],
                       (const __nv_bfloat16*)d_in[7], (const __nv_bfloat16*)d_in[9],
                       (const __nv_bfloat16*)d_in[10], (__nv_bfloat16*)d_out, pace_ns, map_wq, map_w1, map_wo, map_w2);
}
```
